```python
import torch

def _softmax(x, axis=-1):
    return torch.softmax(x, dim=axis)
def _gelu(x):
    return torch.nn.functional.gelu(x, approximate="tanh")
def _silu(x):
    return torch.nn.functional.silu(x)
def _sigmoid(x):
    return torch.sigmoid(x)
def _layernorm(x, axis=-1, eps=1e-5):
    m = x.mean(dim=axis, keepdim=True)
    v = x.var(dim=axis, keepdim=True, unbiased=False)
    return (x - m) / torch.sqrt(v + eps)
def _scatter_add(tgt, idx, src, axis=0):
    return tgt.clone().index_add_(axis, idx, src)
def _segment_sum(src, seg, n):
    out = torch.zeros((n,) + src.shape[1:], dtype=src.dtype)
    return out.index_add_(0, seg, src)
def _pad(x, pw):
    flat = tuple(v for pair in reversed(pw) for v in pair)
    return torch.nn.functional.pad(x, flat)

kernel_name = 'gated_mix__grouped_kv_mqa__moe_arch_mod__prompt'

def setup_inputs():

    _w = (lambda a: (lambda t: t.to(torch.bfloat16) if t.is_floating_point() else t)(torch.as_tensor(a)))
    def _A_setup():
        B, S, D, H = 1, 2048, 576, 32
        Dh = D // H
        return {
            "x": _w((lambda *s: torch.randn(*s, dtype=torch.bfloat16) * 0.05)(B, S, D)),
            "wq": _w((lambda *s: torch.randn(*s, dtype=torch.bfloat16) * 0.8)(D, H * Dh)),
            "wk": _w((lambda *s: torch.randn(*s, dtype=torch.bfloat16) * 0.8)(D, Dh)),
            "wv": _w((lambda *s: torch.randn(*s, dtype=torch.bfloat16) * 0.2)(D, Dh)),
            "wo": _w((lambda *s: torch.randn(*s, dtype=torch.bfloat16) * 0.2)(H * Dh, D)),
        }
    _A_in = _A_setup()

    def _B_setup():
        B, S, D, F, C = 1, 2048, 576, 4608, 1
        return {
            "x": _w((lambda *s: torch.randn(*s, dtype=torch.bfloat16) * 0.05)(B, S, D)),
            "w_r": _w((lambda *s: torch.randn(*s, dtype=torch.bfloat16) * 3.2)(D)),
            "w_gate": _w((lambda *s: torch.randn(*s, dtype=torch.bfloat16) * 0.2)(D, F)),
            "w_up": _w((lambda *s: torch.randn(*s, dtype=torch.bfloat16) * 0.2)(D, F)),
            "w_down": _w((lambda *s: torch.randn(*s, dtype=torch.bfloat16) * 0.2)(F, D)),
        }
    _B_in = _B_setup()

    return {
        "A_x": _A_in["x"],
        "A_wq": _A_in["wq"],
        "A_wk": _A_in["wk"],
        "A_wv": _A_in["wv"],
        "A_wo": _A_in["wo"],
        "B_x": _B_in["x"],
        "B_w_r": _B_in["w_r"],
        "B_w_gate": _B_in["w_gate"],
        "B_w_up": _B_in["w_up"],
        "B_w_down": _B_in["w_down"],
        "gate_w": _w((lambda *s: torch.randn(*s, dtype=torch.bfloat16) * 0.05)(576) * 16.0),
    }

def reference(A_x, A_wq, A_wk, A_wv, A_wo, B_x, B_w_r, B_w_gate, B_w_up, B_w_down, gate_w):
    def _A_ref(x, wq, wk, wv, wo):
        B, S, D = x.shape
        H = 32
        Dh = D // H
        q = (lambda x, *d: x.permute(*d))((x @ wq).reshape(B, S, H, Dh), 0, 2, 1, 3)
        k = x @ wk
        v = x @ wv
        scores = torch.einsum("bhqd,bkd->bhqk", q, k) * (Dh ** -0.5)
        p = _softmax(scores, axis=-1)
        o = torch.einsum("bhqk,bkd->bhqd", p, v)
        return (lambda x, *d: x.permute(*d))(o, 0, 2, 1, 3).reshape(B, S, H * Dh) @ wo

    def _B_ref(x, w_r, w_gate, w_up, w_down):
        B, S, D = x.shape
        C = 1
        r = x @ w_r
        idx = torch.argsort(-r, axis=-1)[:, :C]
        idx_e = (lambda x, n, axis: torch.repeat_interleave(x, n, dim=axis))(idx.reshape(B, C, 1), D, axis=2)
        x_sel = (lambda x, i, axis: torch.take_along_dim(x, i, dim=axis))(x, idx_e, axis=1)
        g = _silu(x_sel @ w_gate)
        u = x_sel @ w_up
        y = (g * u) @ w_down
        r_sel = _sigmoid((lambda x, i, axis: torch.take_along_dim(x, i, dim=axis))(r, idx, axis=1))
        y = y * r_sel.reshape(B, C, 1)
        b_off = (torch.arange(B) * S).reshape(B, 1)
        flat_idx = (idx + b_off).reshape(B * C)
        zero = (x * 0.0).reshape(B * S, D)
        upd = _scatter_add(zero, flat_idx, y.reshape(B * C, D), axis=0)
        return x + upd.reshape(B, S, D)

    x = A_x
    g = _sigmoid((x * gate_w).sum(-1, keepdims=True))
    a = _A_ref(x, A_wq, A_wk, A_wv, A_wo)
    b = _B_ref(x, B_w_r, B_w_gate, B_w_up, B_w_down)
    return g * a + (1 - g) * b
```

```cpp
#include <cuda_runtime.h>
#include <cuda_bf16.h>
#include <stdint.h>

#define S_LEN 2048
#define DM 576
#define FF 4608
#define NCTA 128
#define PMASK 0xB5u

__device__ uint4 g_kv[8 * 1536];
__device__ float4 g_kn[128];
__device__ unsigned long long g_best[128];
__device__ float g_gate[S_LEN];
__device__ __nv_bfloat16 g_o[S_LEN * DM];
__device__ float g_ypart[NCTA * DM];
__device__ unsigned g_ctr[32 * 32];

#define SM_W 98304
#define SM_RED 0
#define SM_MOE1 40960
#define SM_MOE2 57344
#define SM_Q 196608
#define SM_EXT 215040
#define SM_XSEL 224256
#define SM_ERED 226560
#define SM_MBAR 230656
#define SM_MISC 230720
#define SM_TOTAL 231424

__device__ __forceinline__ uint64_t make_desc(uint32_t saddr, uint32_t lbo, uint32_t sbo) {
  return (uint64_t)((saddr & 0x3FFFF) >> 4) | ((uint64_t)(lbo >> 4) << 16) | ((uint64_t)(sbo >> 4) << 32);
}
__device__ __forceinline__ void wg_fence() { asm volatile("wgmma.fence.sync.aligned;" ::: "memory"); }
__device__ __forceinline__ void wg_commit() { asm volatile("wgmma.commit_group.sync.aligned;" ::: "memory"); }
template <int N> __device__ __forceinline__ void wg_wait() { asm volatile("wgmma.wait_group.sync.aligned %0;" ::"n"(N) : "memory"); }
__device__ __forceinline__ void wgmma_n8_t(float (&d)[4], uint32_t a0, uint32_t a1, uint32_t a2, uint32_t a3, uint64_t db, int sd) {
  asm volatile("{\n.reg .pred p;\nsetp.ne.b32 p, %9, 0;\n"
    "wgmma.mma_async.sync.aligned.m64n8k16.f32.bf16.bf16 "
    "{%0,%1,%2,%3}, {%4,%5,%6,%7}, %8, p, 1, 1, 1;\n}\n"
    : "+f"(d[0]),"+f"(d[1]),"+f"(d[2]),"+f"(d[3])
    : "r"(a0),"r"(a1),"r"(a2),"r"(a3),"l"(db),"r"(sd));
}
__device__ __forceinline__ void wgmma_n24_t(float (&d)[12], uint32_t a0, uint32_t a1, uint32_t a2, uint32_t a3, uint64_t db, int sd) {
  asm volatile("{\n.reg .pred p;\nsetp.ne.b32 p, %17, 0;\n"
    "wgmma.mma_async.sync.aligned.m64n24k16.f32.bf16.bf16 "
    "{%0,%1,%2,%3,%4,%5,%6,%7,%8,%9,%10,%11}, {%12,%13,%14,%15}, %16, p, 1, 1, 1;\n}\n"
    : "+f"(d[0]),"+f"(d[1]),"+f"(d[2]),"+f"(d[3]),"+f"(d[4]),"+f"(d[5]),"+f"(d[6]),"+f"(d[7]),"+f"(d[8]),"+f"(d[9]),"+f"(d[10]),"+f"(d[11])
    : "r"(a0),"r"(a1),"r"(a2),"r"(a3),"l"(db),"r"(sd));
}
__device__ __forceinline__ void wgmma_n72_t(float (&d)[36], uint32_t a0, uint32_t a1, uint32_t a2, uint32_t a3, uint64_t db, int sd) {
  asm volatile("{\n.reg .pred p;\nsetp.ne.b32 p, %41, 0;\n"
    "wgmma.mma_async.sync.aligned.m64n72k16.f32.bf16.bf16 "
    "{%0,%1,%2,%3,%4,%5,%6,%7,%8,%9,%10,%11,%12,%13,%14,%15,%16,%17,%18,%19,%20,%21,%22,%23,%24,%25,%26,%27,%28,%29,%30,%31,%32,%33,%34,%35}, {%36,%37,%38,%39}, %40, p, 1, 1, 1;\n}\n"
    : "+f"(d[0]),"+f"(d[1]),"+f"(d[2]),"+f"(d[3]),"+f"(d[4]),"+f"(d[5]),"+f"(d[6]),"+f"(d[7]),"+f"(d[8]),"+f"(d[9]),"+f"(d[10]),"+f"(d[11]),"+f"(d[12]),"+f"(d[13]),"+f"(d[14]),"+f"(d[15]),"+f"(d[16]),"+f"(d[17]),"+f"(d[18]),"+f"(d[19]),"+f"(d[20]),"+f"(d[21]),"+f"(d[22]),"+f"(d[23]),"+f"(d[24]),"+f"(d[25]),"+f"(d[26]),"+f"(d[27]),"+f"(d[28]),"+f"(d[29]),"+f"(d[30]),"+f"(d[31]),"+f"(d[32]),"+f"(d[33]),"+f"(d[34]),"+f"(d[35])
    : "r"(a0),"r"(a1),"r"(a2),"r"(a3),"l"(db),"r"(sd));
}
__device__ __forceinline__ void wgmma_n64_k(float (&d)[32], uint32_t a0, uint32_t a1, uint32_t a2, uint32_t a3, uint64_t db, int sd) {
  asm volatile("{\n.reg .pred p;\nsetp.ne.b32 p, %37, 0;\n"
    "wgmma.mma_async.sync.aligned.m64n64k16.f32.bf16.bf16 "
    "{%0,%1,%2,%3,%4,%5,%6,%7,%8,%9,%10,%11,%12,%13,%14,%15,%16,%17,%18,%19,%20,%21,%22,%23,%24,%25,%26,%27,%28,%29,%30,%31}, {%32,%33,%34,%35}, %36, p, 1, 1, 0;\n}\n"
    : "+f"(d[0]),"+f"(d[1]),"+f"(d[2]),"+f"(d[3]),"+f"(d[4]),"+f"(d[5]),"+f"(d[6]),"+f"(d[7]),"+f"(d[8]),"+f"(d[9]),"+f"(d[10]),"+f"(d[11]),"+f"(d[12]),"+f"(d[13]),"+f"(d[14]),"+f"(d[15]),"+f"(d[16]),"+f"(d[17]),"+f"(d[18]),"+f"(d[19]),"+f"(d[20]),"+f"(d[21]),"+f"(d[22]),"+f"(d[23]),"+f"(d[24]),"+f"(d[25]),"+f"(d[26]),"+f"(d[27]),"+f"(d[28]),"+f"(d[29]),"+f"(d[30]),"+f"(d[31])
    : "r"(a0),"r"(a1),"r"(a2),"r"(a3),"l"(db),"r"(sd));
}

template <int N> __device__ __forceinline__ void fence_regs(float (&s)[N]) {
#pragma unroll
  for (int i = 0; i < N; i++) asm volatile("" : "+f"(s[i])::"memory");
}
template <int N> __device__ __forceinline__ void fence_regs(uint32_t (&s)[N]) {
#pragma unroll
  for (int i = 0; i < N; i++) asm volatile("" : "+r"(s[i])::"memory");
}
__device__ __forceinline__ float ex2(float x) { float r; asm("ex2.approx.ftz.f32 %0, %1;" : "=f"(r) : "f"(x)); return r; }
__device__ __forceinline__ uint32_t pack_bf16(float lo, float hi) { uint32_t r; asm("cvt.rn.bf16x2.f32 %0, %1, %2;" : "=r"(r) : "f"(hi), "f"(lo)); return r; }
__device__ __forceinline__ float bf_lo(uint32_t v) { return __uint_as_float(v << 16); }
__device__ __forceinline__ float bf_hi(uint32_t v) { return __uint_as_float(v & 0xFFFF0000u); }
__device__ __forceinline__ float rbf(float x) { return __bfloat162float(__float2bfloat16_rn(x)); }
__device__ __forceinline__ uint32_t hfma2(uint32_t a, uint32_t b, uint32_t c) { uint32_t r; asm("fma.rn.bf16x2 %0, %1, %2, %3;" : "=r"(r) : "r"(a), "r"(b), "r"(c)); return r; }
template <int LUT> __device__ __forceinline__ uint32_t lop3(uint32_t a, uint32_t b, uint32_t c) { uint32_t r; asm("lop3.b32 %0, %1, %2, %3, %4;" : "=r"(r) : "r"(a), "r"(b), "r"(c), "n"(LUT)); return r; }
__device__ __forceinline__ float sigmoidf_(float x) { return 1.f / (1.f + __expf(-x)); }
__device__ __forceinline__ void bar_sync(int id, int n) { asm volatile("bar.sync %0, %1;" ::"r"(id), "r"(n) : "memory"); }
__device__ __forceinline__ void fence_async() { asm volatile("fence.proxy.async;" ::: "memory"); }
__device__ __forceinline__ void cp_async16(uint32_t dst, const void* src) { asm volatile("cp.async.cg.shared.global [%0], [%1], 16;" ::"r"(dst), "l"(src) : "memory"); }
__device__ __forceinline__ void cp_async_wait_all() { asm volatile("cp.async.wait_all;" ::: "memory"); }
__device__ __forceinline__ uint4 ldg_nc(const void* p) { uint4 v; asm volatile("ld.global.nc.L1::no_allocate.v4.u32 {%0,%1,%2,%3}, [%4];" : "=r"(v.x), "=r"(v.y), "=r"(v.z), "=r"(v.w) : "l"(p)); return v; }
__device__ __forceinline__ uint2 ldg_nc2(const void* p) { uint2 v; asm volatile("ld.global.nc.L1::no_allocate.v2.u32 {%0,%1}, [%2];" : "=r"(v.x), "=r"(v.y) : "l"(p)); return v; }
__device__ __forceinline__ uint4 ldg_cg(const void* p) { uint4 v; asm volatile("ld.global.cg.v4.u32 {%0,%1,%2,%3}, [%4];" : "=r"(v.x), "=r"(v.y), "=r"(v.z), "=r"(v.w) : "l"(p) : "memory"); return v; }
__device__ __forceinline__ void prefetch_l2(const void* p, uint32_t bytes) { asm volatile("cp.async.bulk.prefetch.L2.global [%0], %1;" ::"l"(p), "r"(bytes) : "memory"); }

__device__ __forceinline__ unsigned ticket_arrive(unsigned* ctr, unsigned n) {
  unsigned old;
  asm volatile("fence.acq_rel.gpu;" ::: "memory");
  asm volatile("atom.add.release.gpu.global.u32 %0, [%1], 1;" : "=r"(old) : "l"(ctr) : "memory");
  return (old / n + 1) * n;
}
__device__ __forceinline__ void ticket_wait(unsigned* ctr, unsigned target) {
  for (int it = 0; it < (1 << 22); it++) {
    unsigned v;
    asm volatile("ld.acquire.gpu.global.u32 %0, [%1];" : "=r"(v) : "l"(ctr) : "memory");
    if ((int)(v - target) >= 0) break;
  }
}
__device__ __forceinline__ void mbar_wait(uint32_t bar, uint32_t parity) {
  for (int it = 0; it < (1 << 20); it++) {
    uint32_t ok;
    asm volatile("{\n.reg .pred p;\nmbarrier.try_wait.parity.shared::cta.b64 p, [%1], %2;\nselp.u32 %0, 1, 0, p;\n}\n" : "=r"(ok) : "r"(bar), "r"(parity) : "memory");
    if (ok) break;
  }
}

struct PC { uint32_t one, mone, cb; };
__device__ __forceinline__ uint32_t exp2_sw(float u0, float u1, const PC& pc) {
  uint32_t w = __byte_perm(__float_as_uint(u0), __float_as_uint(u1), 0x6521);
  uint32_t g = lop3<0xEA>(w, 0x007F007Fu, pc.one);
  uint32_t gp = lop3<0xAE>(w, 0x007F007Fu, pc.mone);
  uint32_t t = hfma2(g, gp, 0x3FFF3FFFu);
  uint32_t q = hfma2(g, pc.cb, 0x3E4E3E4Eu);
  uint32_t m = hfma2(t, q, g);
  return lop3<0xD8>(w, m, 0x007F007Fu);
}
template <int HALF> __device__ __forceinline__ void softmax_half(const float (&s)[32], uint32_t (&p)[8], const PC& pc) {
#pragma unroll
  for (int i = 0; i < 4; i++) {
    const int b = HALF * 4 + i;
    if ((PMASK >> b) & 1) {
      p[2 * i] = exp2_sw(s[4 * b], s[4 * b + 1], pc);
      p[2 * i + 1] = exp2_sw(s[4 * b + 2], s[4 * b + 3], pc);
    } else {
      p[2 * i] = pack_bf16(ex2(s[4 * b]), ex2(s[4 * b + 1]));
      p[2 * i + 1] = pack_bf16(ex2(s[4 * b + 2]), ex2(s[4 * b + 3]));
    }
  }
}
__device__ __forceinline__ uint32_t tile_off(int t) { return (uint32_t)((t >> 2) * 1536 + (t & 3) * 192); }

__device__ __forceinline__ void qk(float (&s)[32], const uint32_t (&q)[6], uint64_t kd0, uint64_t kd1, uint32_t off) {
  wgmma_n64_k(s, q[0], q[1], q[2], q[3], kd0 + off, 0);
  wgmma_n64_k(s, q[4], q[5], 0u, 0u, kd1 + off, 1);
}
__device__ __forceinline__ void pv(float (&o)[12], const uint32_t (&p)[16], uint64_t vd, uint32_t off) {
#pragma unroll
  for (int k = 0; k < 4; k++) wgmma_n24_t(o, p[4 * k], p[4 * k + 1], p[4 * k + 2], p[4 * k + 3], vd + off + k * 48, 1);
}

__device__ __forceinline__ void pv_half(float (&o)[12], const uint32_t (&p)[8], uint64_t vd, uint32_t off) {
  wgmma_n24_t(o, p[0], p[1], p[2], p[3], vd + off, 1);
  wgmma_n24_t(o, p[4], p[5], p[6], p[7], vd + off + 48, 1);
}
__device__ __forceinline__ void attn_step(float (&sc)[32], float (&sn)[32], uint32_t (&pl)[8], uint32_t (&ph)[8], float (&o)[12],
                                          const uint32_t (&q)[6], uint64_t kd0, uint64_t kd1, uint64_t vd, uint32_t offc, uint32_t offn, const PC& pc) {
  wg_fence();
  qk(sn, q, kd0, kd1, offn);
  wg_commit();
  wg_wait<2>();
  fence_regs(sc); fence_regs(pl);
  softmax_half<0>(sc, pl, pc);
  fence_regs(pl);
  wg_fence();
  pv_half(o, pl, vd, offc);
  wg_commit();
  wg_wait<2>();
  fence_regs(ph);
  softmax_half<1>(sc, ph, pc);
  fence_regs(ph);
  wg_fence();
  pv_half(o, ph, vd, offc + 96);
  wg_commit();
}
__device__ __forceinline__ void attn_fast(const uint32_t (&q)[6], float (&o)[12], uint32_t sb, const PC& pc) {
  const uint64_t kd0 = make_desc(sb, 128, 384), kd1 = make_desc(sb + 256, 0, 384), vd = make_desc(sb + 12288, 384, 128);
  float sA[32], sB[32];
  uint32_t pl[8], ph[8];
#pragma unroll
  for (int i = 0; i < 12; i++) o[i] = 0.f;
#pragma unroll
  for (int i = 0; i < 8; i++) { pl[i] = 0u; ph[i] = 0u; }
  mbar_wait(sb + SM_MBAR, 0);
  wg_fence();
  qk(sA, q, kd0, kd1, 0);
  wg_commit();
  wg_wait<0>();
  fence_regs(sA);
#pragma unroll 1
  for (int t = 0; t < 32; t += 2) {
    const uint32_t off = tile_off(t);
    attn_step(sA, sB, pl, ph, o, q, kd0, kd1, vd, off, off + 192, pc);
    const int t2 = (t + 2) & 31;
    if ((t2 & 3) == 0) mbar_wait(sb + SM_MBAR + (t2 >> 2) * 8, 0);
    attn_step(sB, sA, pl, ph, o, q, kd0, kd1, vd, off + 192, tile_off(t2), pc);
  }
  wg_wait<0>();
  fence_regs(o); fence_regs(pl); fence_regs(ph); fence_regs(sA);
}

__device__ __forceinline__ void attn_safe(const uint32_t (&q)[6], float (&o)[12], uint32_t sb) {
  const uint64_t kd0 = make_desc(sb, 128, 384), kd1 = make_desc(sb + 256, 0, 384), vd = make_desc(sb + 12288, 384, 128);
  float s[32];
  uint32_t p[16];
  float m0 = -INFINITY, m1 = -INFINITY;
#pragma unroll
  for (int i = 0; i < 12; i++) o[i] = 0.f;
#pragma unroll 1
  for (int t = 0; t < 32; t++) {
    if ((t & 3) == 0) mbar_wait(sb + SM_MBAR + (t >> 2) * 8, 0);
    wg_fence();
    qk(s, q, kd0, kd1, tile_off(t));
    wg_commit();
    wg_wait<0>();
    fence_regs(s);
#pragma unroll
    for (int b = 0; b < 8; b++) {
      const float sc = ((PMASK >> b) & 1) ? 0.5f : 1.f;
      m0 = fmaxf(m0, sc * fmaxf(s[4 * b], s[4 * b + 1]));
      m1 = fmaxf(m1, sc * fmaxf(s[4 * b + 2], s[4 * b + 3]));
    }
  }
  m0 = fmaxf(m0, __shfl_xor_sync(~0u, m0, 1)); m0 = fmaxf(m0, __shfl_xor_sync(~0u, m0, 2));
  m1 = fmaxf(m1, __shfl_xor_sync(~0u, m1, 1)); m1 = fmaxf(m1, __shfl_xor_sync(~0u, m1, 2));
#pragma unroll 1
  for (int t = 0; t < 32; t++) {
    wg_fence();
    qk(s, q, kd0, kd1, tile_off(t));
    wg_commit();
    wg_wait<0>();
    fence_regs(s);
#pragma unroll
    for (int b = 0; b < 8; b++) {
      const float sc = ((PMASK >> b) & 1) ? 0.5f : 1.f;
      p[2 * b] = pack_bf16(ex2(fmaf(s[4 * b], sc, -m0)), ex2(fmaf(s[4 * b + 1], sc, -m0)));
      p[2 * b + 1] = pack_bf16(ex2(fmaf(s[4 * b + 2], sc, -m1)), ex2(fmaf(s[4 * b + 3], sc, -m1)));
    }
    fence_regs(p);
    wg_fence();
    pv(o, p, vd, tile_off(t));
    wg_commit();
    wg_wait<0>();
    fence_regs(o); fence_regs(p);
  }
}

__device__ __forceinline__ void stage_w(uint32_t sb, const __nv_bfloat16* w, int hg, int tid) {
#pragma unroll
  for (int i = 0; i < 11; i++) {
    int idx = tid + 512 * i;
    if (idx < 5184) {
      int k = idx / 9, nb = idx - k * 9;
      int kg = (k >> 5) * 4 + ((k & 7) >> 1), r = ((k >> 3) & 3) * 2 + (k & 1);
      cp_async16(sb + SM_W + kg * 1296 + nb * 144 + r * 16, w + k * DM + hg * 72 + nb * 8);
    }
  }
}
__device__ __forceinline__ void gemm72(float (&acc)[36], const uint4 (&xa)[9][2], uint32_t sb, int kh) {
  const uint64_t wd = make_desc(sb + SM_W + kh * 36 * 1296, 1296, 144);
  wg_fence();
#pragma unroll
  for (int j = 0; j < 9; j++) {
    wgmma_n72_t(acc, xa[j][0].x, xa[j][1].x, xa[j][0].y, xa[j][1].y, wd + (uint64_t)(j * 4 * 81), j > 0);
    wgmma_n72_t(acc, xa[j][0].z, xa[j][1].z, xa[j][0].w, xa[j][1].w, wd + (uint64_t)(j * 4 * 81 + 162), 1);
  }
  wg_commit();
  wg_wait<0>();
  fence_regs(acc);
}
__device__ __forceinline__ void ksplit_reduce(float (&acc)[36], uint8_t* smem, int mh, int kh, int t128) {
  float* red = (float*)(smem + SM_RED) + mh * 36 * 128 + t128;
  if (kh == 0) {
#pragma unroll
    for (int i = 20; i < 36; i++) red[i * 128] = acc[i];
  } else {
#pragma unroll
    for (int i = 0; i < 20; i++) red[i * 128] = acc[i];
  }
  bar_sync(1 + mh, 256);
  if (kh == 0) {
#pragma unroll
    for (int i = 0; i < 20; i++) acc[i] += red[i * 128];
  } else {
#pragma unroll
    for (int i = 20; i < 36; i++) acc[i] += red[i * 128];
  }
}

__global__ void __launch_bounds__(512, 1)
fused_kernel(const __nv_bfloat16* __restrict__ x, const __nv_bfloat16* __restrict__ wq, const __nv_bfloat16* __restrict__ wk,
             const __nv_bfloat16* __restrict__ wv, const __nv_bfloat16* __restrict__ wo, const __nv_bfloat16* __restrict__ w_r,
             const __nv_bfloat16* __restrict__ w_gate, const __nv_bfloat16* __restrict__ w_up, const __nv_bfloat16* __restrict__ w_down,
             const __nv_bfloat16* __restrict__ gate_w, __nv_bfloat16* __restrict__ out, uint32_t zero) {
  extern __shared__ __align__(1024) uint8_t smem[];
  const uint32_t sb = (uint32_t)__cvta_generic_to_shared(smem);
  const int tid = threadIdx.x, wg = tid >> 7, wi = (tid >> 5) & 3, lane = tid & 31, g = lane >> 2, c = lane & 3;
  const int bid = blockIdx.x, tb = bid >> 3, hg = bid & 7;
  const int mh = wg & 1, kh = wg >> 1, t128 = tid & 127;
  const int lrow = mh * 64 + wi * 16 + g;
  unsigned tgt_kv = 0;

  if (tid == 0) {
#pragma unroll
    for (int i = 0; i < 8; i++) asm volatile("mbarrier.init.shared::cta.b64 [%0], 1;" ::"r"(sb + SM_MBAR + i * 8) : "memory");
    if (hg >= 6) tgt_kv = ticket_arrive(&g_ctr[0], NCTA);
  }
  uint4 xa[9][2];
  {
    uint4 ev[2];
    if (hg < 6) {
#pragma unroll
      for (int i = 0; i < 2; i++) {
        int k = tid + 512 * i;
        ev[i] = make_uint4(0, 0, 0, 0);
        if (k < DM) {
          const uint32_t* src = (const uint32_t*)((hg < 3 ? wk : wv) + k * 18) + (hg % 3) * 4;
          ev[i].x = __ldg(src);
          if (hg % 3 != 2) { ev[i].y = __ldg(src + 1); ev[i].z = __ldg(src + 2); ev[i].w = __ldg(src + 3); }
          else if (hg == 2) ev[i].y = (uint32_t)__bfloat16_as_ushort(w_r[k]) | ((uint32_t)__bfloat16_as_ushort(gate_w[k]) << 16);
        }
      }
    }
    const __nv_bfloat16* xp = x + (size_t)(tb * 128 + lrow) * DM + kh * 288 + c * 8;
#pragma unroll
    for (int j = 0; j < 9; j++) { xa[j][0] = ldg_nc(xp + j * 32); xa[j][1] = ldg_nc(xp + 8 * DM + j * 32); }
    stage_w(sb, wq, hg, tid);
    if (hg < 6) {
#pragma unroll
      for (int i = 0; i < 2; i++) {
        int k = tid + 512 * i;
        if (k < DM) {
          int kg = (k >> 5) * 4 + ((k & 7) >> 1), r = ((k >> 3) & 3) * 2 + (k & 1);
          *(uint4*)(smem + SM_EXT + kg * 128 + r * 16) = ev[i];
        }
      }
    }
  }
  fence_async();
  __syncthreads();
  if (hg < 6) {
    float e[4];
    const uint64_t ed = make_desc(sb + SM_EXT + kh * 36 * 128, 128, 128);
    wg_fence();
#pragma unroll
    for (int j = 0; j < 9; j++) {
      wgmma_n8_t(e, xa[j][0].x, xa[j][1].x, xa[j][0].y, xa[j][1].y, ed + (uint64_t)(j * 32), j > 0);
      wgmma_n8_t(e, xa[j][0].z, xa[j][1].z, xa[j][0].w, xa[j][1].w, ed + (uint64_t)(j * 32 + 16), 1);
    }
    wg_commit();
    wg_wait<0>();
    fence_regs(e);
    float4* er = (float4*)(smem + SM_ERED) + mh * 128 + t128;
    if (kh == 1) *er = make_float4(e[0], e[1], e[2], e[3]);
    bar_sync(1 + mh, 256);
    if (kh == 0) {
      float4 o4 = *er;
      e[0] += o4.x; e[1] += o4.y; e[2] += o4.z; e[3] += o4.w;
      const int ch = hg % 3;
      float nrm = 0.f;
      unsigned long long best = 0ull;
#pragma unroll
      for (int h = 0; h < 2; h++) {
        const int key = tb * 128 + lrow + 8 * h;
        const bool poly = (PMASK >> ((key >> 3) & 7)) & 1;
        uint32_t v = pack_bf16(e[2 * h], e[2 * h + 1]);
        if (hg < 3) {
          float lo = bf_lo(v), hi = bf_hi(v);
          float n2 = (hg == 2 && c != 0) ? 0.f : lo * lo + hi * hi;
          n2 += __shfl_xor_sync(~0u, n2, 1);
          n2 += __shfl_xor_sync(~0u, n2, 2);
          nrm = fmaxf(nrm, n2);
          if (hg == 2 && c == 1) {
            g_gate[key] = rbf(sigmoidf_(hi));
            uint32_t rb = __float_as_uint(lo);
            rb = (rb & 0x80000000u) ? ~rb : (rb | 0x80000000u);
            unsigned long long cand = ((unsigned long long)rb << 32) | (uint32_t)(~key);
            best = cand > best ? cand : best;
          }
          if (poly) v = pack_bf16(2.f * lo, 2.f * hi);
          if (hg == 2 && c != 0) v = c == 1 ? (poly ? 0x44404000u : 0x00003F80u) : (c == 2 && poly ? 0x0000BFFFu : 0u);
        } else if (hg == 5 && c != 0) {
          v = c == 1 ? 0x00003F80u : 0u;
        }
        uint8_t* dst = (uint8_t*)g_kv + (key >> 8) * 24576 + (hg >= 3 ? 12288 : 0) + ((key >> 3) & 31) * 384 + ch * 128 + (key & 7) * 16 + c * 4;
        *(uint32_t*)dst = v;
      }
      if (hg < 3) {
#pragma unroll
        for (int o = 4; o < 32; o <<= 1) nrm = fmaxf(nrm, __shfl_xor_sync(~0u, nrm, o));
        if (lane == 0) ((float*)&g_kn[tb * 8 + mh * 4 + wi])[hg] = nrm;
        if (hg == 2) {
#pragma unroll
          for (int o = 1; o < 32; o <<= 1) { unsigned long long b2 = __shfl_xor_sync(~0u, best, o); best = b2 > best ? b2 : best; }
          if (lane == 0) g_best[tb * 8 + mh * 4 + wi] = best;
        }
      }
      fence_async();
      bar_sync(3, 256);
      if (tid == 0) tgt_kv = ticket_arrive(&g_ctr[0], NCTA);
    }
  }
  cp_async_wait_all();
  fence_async();
  __syncthreads();
  {
    float acc[36];
    gemm72(acc, xa, sb, kh);
    ksplit_reduce(acc, smem, mh, kh, t128);
    const float qs = 0.23570226039551584f * 1.4426950408889634f;
    uint8_t* qp = smem + SM_Q + lrow * 144 + c * 4;
#pragma unroll
    for (int nb = 0; nb < 9; nb++) {
      if ((nb < 5) == (kh == 0)) {
        *(uint32_t*)(qp + nb * 16) = pack_bf16(acc[4 * nb] * qs, acc[4 * nb + 1] * qs);
        *(uint32_t*)(qp + 8 * 144 + nb * 16) = pack_bf16(acc[4 * nb + 2] * qs, acc[4 * nb + 3] * qs);
      }
    }
  }
  fence_async();
  __syncthreads();
  if (tid == 0) {
    ticket_wait(&g_ctr[0], tgt_kv);
    fence_async();
#pragma unroll
    for (int i = 0; i < 8; i++) {
      asm volatile("mbarrier.arrive.expect_tx.shared::cta.b64 _, [%0], 24576;" ::"r"(sb + SM_MBAR + i * 8) : "memory");
      asm volatile("cp.async.bulk.shared::cluster.global.mbarrier::complete_tx::bytes [%0], [%1], 24576, [%2];"
                   ::"r"(sb + i * 24576), "l"((const uint8_t*)g_kv + i * 24576), "r"(sb + SM_MBAR + i * 8) : "memory");
    }
    prefetch_l2((const uint8_t*)wo + bid * 5184, 5184);
    prefetch_l2((const uint8_t*)w_gate + bid * 41472, 41472);
    prefetch_l2((const uint8_t*)w_up + bid * 41472, 41472);
    prefetch_l2((const uint8_t*)w_down + bid * 41472, 41472);
  }
  __syncthreads();

  {
    float kmax = 0.f;
#pragma unroll
    for (int i = 0; i < 4; i++) { float4 v = g_kn[lane + 32 * i]; kmax = fmaxf(kmax, v.x + v.y + v.z); }
#pragma unroll
    for (int o = 1; o < 32; o <<= 1) kmax = fmaxf(kmax, __shfl_xor_sync(~0u, kmax, o));
    PC pc; pc.one = 0x3F803F80u + zero; pc.mone = 0xBF80BF80u + zero; pc.cb = 0x3DCD3DCDu + zero;
#pragma unroll 1
    for (int pass = 0; pass < 2; pass++) {
      const int r0 = pass * 64 + wi * 16 + g;
      const uint8_t* qp = smem + SM_Q + r0 * 144 + wg * 36 + c * 4;
      uint32_t q[6];
      q[0] = *(const uint32_t*)qp; q[1] = *(const uint32_t*)(qp + 8 * 144);
      q[2] = *(const uint32_t*)(qp + 16); q[3] = *(const uint32_t*)(qp + 8 * 144 + 16);
      q[4] = c == 0 ? *(const uint32_t*)(qp + 32) : 0u; q[5] = c == 0 ? *(const uint32_t*)(qp + 8 * 144 + 32) : 0u;
      float n0 = bf_lo(q[0]) * bf_lo(q[0]) + bf_hi(q[0]) * bf_hi(q[0]) + bf_lo(q[2]) * bf_lo(q[2]) + bf_hi(q[2]) * bf_hi(q[2]) + bf_lo(q[4]) * bf_lo(q[4]) + bf_hi(q[4]) * bf_hi(q[4]);
      float n1 = bf_lo(q[1]) * bf_lo(q[1]) + bf_hi(q[1]) * bf_hi(q[1]) + bf_lo(q[3]) * bf_lo(q[3]) + bf_hi(q[3]) * bf_hi(q[3]) + bf_lo(q[5]) * bf_lo(q[5]) + bf_hi(q[5]) * bf_hi(q[5]);
      n0 += __shfl_xor_sync(~0u, n0, 1); n0 += __shfl_xor_sync(~0u, n0, 2);
      n1 += __shfl_xor_sync(~0u, n1, 1); n1 += __shfl_xor_sync(~0u, n1, 2);
      const float m0 = ceilf(sqrtf(n0 * kmax) * 1.001f + 0.01f), m1 = ceilf(sqrtf(n1 * kmax) * 1.001f + 0.01f);
      uint32_t unsafe;
      asm volatile("{\n.reg .pred p, r;\nsetp.ne.u32 p, %1, 0;\nbarrier.cta.red.or.pred.aligned r, %2, 128, p;\nselp.u32 %0, 1, 0, r;\n}\n"
                   : "=r"(unsafe) : "r"((uint32_t)!(m0 <= 60.f && m1 <= 60.f)), "r"(4 + wg) : "memory");
      float o[12];
      if (!unsafe) {
        if (c == 1) { q[4] = pack_bf16(-m0, 1.f); q[5] = pack_bf16(-m1, 1.f); }
        if (c == 2) { q[4] = 0x3F803F80u; q[5] = 0x3F803F80u; }
        attn_fast(q, o, sb, pc);
      } else {
        attn_safe(q, o, sb);
      }
      const float i0 = 1.f / __shfl_sync(~0u, o[8], (lane & ~3) | 1), i1 = 1.f / __shfl_sync(~0u, o[10], (lane & ~3) | 1);
      uint32_t* op = (uint32_t*)(g_o + (size_t)(tb * 128 + r0) * DM + hg * 72 + wg * 18) + c;
      op[0] = pack_bf16(o[0] * i0, o[1] * i0); op[4 * DM] = pack_bf16(o[2] * i1, o[3] * i1);
      op[4] = pack_bf16(o[4] * i0, o[5] * i0); op[4 * DM + 4] = pack_bf16(o[6] * i1, o[7] * i1);
      if (c == 0) { op[8] = pack_bf16(o[8] * i0, o[9] * i0); op[4 * DM + 8] = pack_bf16(o[10] * i1, o[11] * i1); }
    }
  }
  __syncthreads();
  unsigned tgt_o = 0, tgt_y = 0;
  if (tid == 0) tgt_o = ticket_arrive(&g_ctr[32 * (1 + tb)], 8);
  stage_w(sb, wo, hg, tid);

  int sel;
  float rsel;
  {
    uint2 wgv[12], wuv[12];
    uint4 wdv[6];
    const int q9 = tid % 9, rg = tid / 9, c72 = tid % 72, r6 = tid / 72;
    if (tid < 432) {
#pragma unroll
      for (int i = 0; i < 12; i++) {
        size_t off = (size_t)(rg + 48 * i) * FF + bid * 36 + q9 * 4;
        wgv[i] = ldg_nc2(w_gate + off); wuv[i] = ldg_nc2(w_up + off);
      }
#pragma unroll
      for (int i = 0; i < 6; i++) wdv[i] = ldg_nc(w_down + (size_t)(bid * 36 + r6 * 6 + i) * DM + c72 * 8);
    }
    unsigned long long best = 0ull;
#pragma unroll
    for (int i = 0; i < 4; i++) { unsigned long long b2 = g_best[lane + 32 * i]; best = b2 > best ? b2 : best; }
#pragma unroll
    for (int o = 1; o < 32; o <<= 1) { unsigned long long b2 = __shfl_xor_sync(~0u, best, o); best = b2 > best ? b2 : best; }
    sel = (int)(~(uint32_t)best) & (S_LEN - 1);
    uint32_t rb = (uint32_t)(best >> 32);
    rb = (rb & 0x80000000u) ? (rb & 0x7FFFFFFFu) : ~rb;
    rsel = rbf(sigmoidf_(__uint_as_float(rb)));
    float* m1 = (float*)(smem + SM_MOE1);
    float* m2 = (float*)(smem + SM_MOE2);
    float* hs = (float*)(smem + SM_MISC);
    if (tid < 432) {
      float ga[4] = {0.f, 0.f, 0.f, 0.f}, ua[4] = {0.f, 0.f, 0.f, 0.f};
#pragma unroll
      for (int i = 0; i < 12; i++) {
        float xv = __bfloat162float(x[(size_t)sel * DM + rg + 48 * i]);
        ga[0] = fmaf(xv, bf_lo(wgv[i].x), ga[0]); ga[1] = fmaf(xv, bf_hi(wgv[i].x), ga[1]);
        ga[2] = fmaf(xv, bf_lo(wgv[i].y), ga[2]); ga[3] = fmaf(xv, bf_hi(wgv[i].y), ga[3]);
        ua[0] = fmaf(xv, bf_lo(wuv[i].x), ua[0]); ua[1] = fmaf(xv, bf_hi(wuv[i].x), ua[1]);
        ua[2] = fmaf(xv, bf_lo(wuv[i].y), ua[2]); ua[3] = fmaf(xv, bf_hi(wuv[i].y), ua[3]);
      }
      *(float4*)(m1 + rg * 72 + q9 * 4) = make_float4(ga[0], ga[1], ga[2], ga[3]);
      *(float4*)(m1 + rg * 72 + 36 + q9 * 4) = make_float4(ua[0], ua[1], ua[2], ua[3]);
    }
    __syncthreads();
    if (tid < 432) {
      float s = 0.f;
#pragma unroll
      for (int i = 0; i < 8; i++) s += m1[(r6 * 8 + i) * 72 + c72];
      m2[r6 * 72 + c72] = s;
    }
    __syncthreads();
    if (tid < 36) {
      float gs = 0.f, us = 0.f;
#pragma unroll
      for (int i = 0; i < 6; i++) { gs += m2[i * 72 + tid]; us += m2[i * 72 + 36 + tid]; }
      gs = rbf(gs); us = rbf(us);
      hs[tid] = rbf(rbf(gs * sigmoidf_(gs)) * us);
    }
    __syncthreads();
    if (tid < 432) {
      float y[8] = {0.f, 0.f, 0.f, 0.f, 0.f, 0.f, 0.f, 0.f};
#pragma unroll
      for (int i = 0; i < 6; i++) {
        float hv = hs[r6 * 6 + i];
        y[0] = fmaf(hv, bf_lo(wdv[i].x), y[0]); y[1] = fmaf(hv, bf_hi(wdv[i].x), y[1]);
        y[2] = fmaf(hv, bf_lo(wdv[i].y), y[2]); y[3] = fmaf(hv, bf_hi(wdv[i].y), y[3]);
        y[4] = fmaf(hv, bf_lo(wdv[i].z), y[4]); y[5] = fmaf(hv, bf_hi(wdv[i].z), y[5]);
        y[6] = fmaf(hv, bf_lo(wdv[i].w), y[6]); y[7] = fmaf(hv, bf_hi(wdv[i].w), y[7]);
      }
      *(float4*)(m1 + r6 * DM + c72 * 8) = make_float4(y[0], y[1], y[2], y[3]);
      *(float4*)(m1 + r6 * DM + c72 * 8 + 4) = make_float4(y[4], y[5], y[6], y[7]);
    }
    __syncthreads();
    if (tid < 288) {
      float2 s = make_float2(0.f, 0.f);
#pragma unroll
      for (int i = 0; i < 6; i++) { float2 v = *(float2*)(m1 + i * DM + tid * 2); s.x += v.x; s.y += v.y; }
      *(float2*)(g_ypart + bid * DM + tid * 2) = s;
    }
    __syncthreads();
    if (tid == 0) {
      tgt_y = ticket_arrive(&g_ctr[32 * 17], NCTA);
      ticket_wait(&g_ctr[32 * (1 + tb)], tgt_o);
    }
  }
  cp_async_wait_all();
  fence_async();
  __syncthreads();

  {
    const __nv_bfloat16* ap = g_o + (size_t)(tb * 128 + lrow) * DM + kh * 288 + c * 8;
#pragma unroll
    for (int j = 0; j < 9; j++) { xa[j][0] = ldg_cg(ap + j * 32); xa[j][1] = ldg_cg(ap + 8 * DM + j * 32); }
    const int row = tb * 128 + lrow;
    const int nb0 = kh == 0 ? 0 : 5;
    uint32_t xr[5][2];
    const uint32_t* xp = (const uint32_t*)(x + (size_t)row * DM + hg * 72 + nb0 * 8) + c;
#pragma unroll
    for (int i = 0; i < 5; i++) {
      if (i < 4 || kh == 0) { xr[i][0] = __ldg(xp + i * 4); xr[i][1] = __ldg(xp + 4 * DM + i * 4); }
    }
    const float g0 = g_gate[row], g1 = g_gate[row + 8];
    float acc[36];
    gemm72(acc, xa, sb, kh);
    ksplit_reduce(acc, smem, mh, kh, t128);
    float* upd = (float*)(smem + SM_MISC);
    const bool owner = (sel >> 7) == tb;
    if (owner) {
      float* m2 = (float*)(smem + SM_MOE2);
      if (tid == 0) ticket_wait(&g_ctr[32 * 17], tgt_y);
      __syncthreads();
      if (tid < 288) {
        const int c72 = tid % 72, pt = tid / 72;
        float s = 0.f;
#pragma unroll 8
        for (int i = 0; i < 32; i++) s += __ldcg(g_ypart + (pt * 32 + i) * DM + hg * 72 + c72);
        m2[tid] = s;
      }
      __syncthreads();
      if (tid < 72) upd[tid] = rbf(rbf(m2[tid] + m2[72 + tid] + m2[144 + tid] + m2[216 + tid]) * rsel);
      __syncthreads();
    }
    const float h0 = rbf(1.f - g0), h1 = rbf(1.f - g1);
    uint32_t* op = (uint32_t*)(out + (size_t)row * DM + hg * 72 + nb0 * 8) + c;
#pragma unroll
    for (int i = 0; i < 5; i++) {
      if (i < 4 || kh == 0) {
        float a0, a1, a2, a3;
        if (kh == 0) { a0 = acc[4 * i]; a1 = acc[4 * i + 1]; a2 = acc[4 * i + 2]; a3 = acc[4 * i + 3]; }
        else { const int j = i < 4 ? 20 + 4 * i : 20; a0 = acc[j]; a1 = acc[j + 1]; a2 = acc[j + 2]; a3 = acc[j + 3]; }
        float b0 = bf_lo(xr[i][0]), b1 = bf_hi(xr[i][0]), b2 = bf_lo(xr[i][1]), b3 = bf_hi(xr[i][1]);
        if (owner) {
          const int col = (nb0 + i) * 8 + c * 2;
          if (row == sel) { b0 = rbf(b0 + upd[col]); b1 = rbf(b1 + upd[col + 1]); }
          if (row + 8 == sel) { b2 = rbf(b2 + upd[col]); b3 = rbf(b3 + upd[col + 1]); }
        }
        op[i * 4] = pack_bf16(rbf(g0 * rbf(a0)) + rbf(h0 * b0), rbf(g0 * rbf(a1)) + rbf(h0 * b1));
        op[4 * DM + i * 4] = pack_bf16(rbf(g1 * rbf(a2)) + rbf(h1 * b2), rbf(g1 * rbf(a3)) + rbf(h1 * b3));
      }
    }
  }
}

extern "C" void kernel_launch(void* const* d_in, const int* in_sizes, int n_in, void* d_out, int out_size) {
  cudaFuncSetAttribute(fused_kernel, cudaFuncAttributeMaxDynamicSharedMemorySize, SM_TOTAL);
  typedef const __nv_bfloat16* P;
  fused_kernel<<<NCTA, 512, SM_TOTAL, cudaStreamPerThread>>>((P)d_in[0], (P)d_in[1], (P)d_in[2], (P)d_in[3], (P)d_in[4], (P)d_in[6],
                                                            (P)d_in[7], (P)d_in[8], (P)d_in[9], (P)d_in[10], (__nv_bfloat16*)d_out, 0u);
}
```

```cpp
#include <cuda_runtime.h>
#include <cuda_bf16.h>
#include <stdint.h>

#define S_LEN 2048
#define DM 576
#define FF 4608
#define NCTA 128
#define PMASK 0xB5u

__device__ uint4 g_kv[8 * 1536];
__device__ float4 g_kn[128];
__device__ unsigned long long g_best[128];
__device__ float g_gate[S_LEN];
__device__ uint4 g_o[S_LEN * DM / 8];
__device__ float g_ypart[NCTA * DM];
__device__ unsigned g_ctr[32 * 32];

#define SM_W 98304
#define SM_W3 147456
#define SM_RED 0
#define SM_MOE1 40960
#define SM_MOE2 57344
#define SM_Q 196608
#define SM_EXT 215040
#define SM_XSEL 224256
#define SM_ERED 226560
#define SM_MBAR 230656
#define SM_MISC 230720
#define SM_TOTAL 231424

__device__ __forceinline__ uint64_t make_desc(uint32_t saddr, uint32_t lbo, uint32_t sbo) {
  return (uint64_t)((saddr & 0x3FFFF) >> 4) | ((uint64_t)(lbo >> 4) << 16) | ((uint64_t)(sbo >> 4) << 32);
}
__device__ __forceinline__ void wg_fence() { asm volatile("wgmma.fence.sync.aligned;" ::: "memory"); }
__device__ __forceinline__ void wg_commit() { asm volatile("wgmma.commit_group.sync.aligned;" ::: "memory"); }
template <int N> __device__ __forceinline__ void wg_wait() { asm volatile("wgmma.wait_group.sync.aligned %0;" ::"n"(N) : "memory"); }
__device__ __forceinline__ void wgmma_t(float (&d)[4], uint32_t a0, uint32_t a1, uint32_t a2, uint32_t a3, uint64_t db, int sd) {
  asm volatile("{\n.reg .pred p;\nsetp.ne.b32 p, %9, 0;\n"
    "wgmma.mma_async.sync.aligned.m64n8k16.f32.bf16.bf16 "
    "{%0,%1,%2,%3}, {%4,%5,%6,%7}, %8, p, 1, 1, 1;\n}\n"
    : "+f"(d[0]),"+f"(d[1]),"+f"(d[2]),"+f"(d[3])
    : "r"(a0),"r"(a1),"r"(a2),"r"(a3),"l"(db),"r"(sd));
}
__device__ __forceinline__ void wgmma_t(float (&d)[4], uint64_t da, uint64_t db, int sd) {
  asm volatile("{\n.reg .pred p;\nsetp.ne.b32 p, %6, 0;\n"
    "wgmma.mma_async.sync.aligned.m64n8k16.f32.bf16.bf16 "
    "{%0,%1,%2,%3}, %4, %5, p, 1, 1, 0, 1;\n}\n"
    : "+f"(d[0]),"+f"(d[1]),"+f"(d[2]),"+f"(d[3])
    : "l"(da),"l"(db),"r"(sd));
}
__device__ __forceinline__ void wgmma_n24_t(float (&d)[12], uint32_t a0, uint32_t a1, uint32_t a2, uint32_t a3, uint64_t db, int sd) {
  asm volatile("{\n.reg .pred p;\nsetp.ne.b32 p, %17, 0;\n"
    "wgmma.mma_async.sync.aligned.m64n24k16.f32.bf16.bf16 "
    "{%0,%1,%2,%3,%4,%5,%6,%7,%8,%9,%10,%11}, {%12,%13,%14,%15}, %16, p, 1, 1, 1;\n}\n"
    : "+f"(d[0]),"+f"(d[1]),"+f"(d[2]),"+f"(d[3]),"+f"(d[4]),"+f"(d[5]),"+f"(d[6]),"+f"(d[7]),"+f"(d[8]),"+f"(d[9]),"+f"(d[10]),"+f"(d[11])
    : "r"(a0),"r"(a1),"r"(a2),"r"(a3),"l"(db),"r"(sd));
}
__device__ __forceinline__ void wgmma_t(float (&d)[36], uint32_t a0, uint32_t a1, uint32_t a2, uint32_t a3, uint64_t db, int sd) {
  asm volatile("{\n.reg .pred p;\nsetp.ne.b32 p, %41, 0;\n"
    "wgmma.mma_async.sync.aligned.m64n72k16.f32.bf16.bf16 "
    "{%0,%1,%2,%3,%4,%5,%6,%7,%8,%9,%10,%11,%12,%13,%14,%15,%16,%17,%18,%19,%20,%21,%22,%23,%24,%25,%26,%27,%28,%29,%30,%31,%32,%33,%34,%35}, {%36,%37,%38,%39}, %40, p, 1, 1, 1;\n}\n"
    : "+f"(d[0]),"+f"(d[1]),"+f"(d[2]),"+f"(d[3]),"+f"(d[4]),"+f"(d[5]),"+f"(d[6]),"+f"(d[7]),"+f"(d[8]),"+f"(d[9]),"+f"(d[10]),"+f"(d[11]),"+f"(d[12]),"+f"(d[13]),"+f"(d[14]),"+f"(d[15]),"+f"(d[16]),"+f"(d[17]),"+f"(d[18]),"+f"(d[19]),"+f"(d[20]),"+f"(d[21]),"+f"(d[22]),"+f"(d[23]),"+f"(d[24]),"+f"(d[25]),"+f"(d[26]),"+f"(d[27]),"+f"(d[28]),"+f"(d[29]),"+f"(d[30]),"+f"(d[31]),"+f"(d[32]),"+f"(d[33]),"+f"(d[34]),"+f"(d[35])
    : "r"(a0),"r"(a1),"r"(a2),"r"(a3),"l"(db),"r"(sd));
}
__device__ __forceinline__ void wgmma_t(float (&d)[36], uint64_t da, uint64_t db, int sd) {
  asm volatile("{\n.reg .pred p;\nsetp.ne.b32 p, %38, 0;\n"
    "wgmma.mma_async.sync.aligned.m64n72k16.f32.bf16.bf16 "
    "{%0,%1,%2,%3,%4,%5,%6,%7,%8,%9,%10,%11,%12,%13,%14,%15,%16,%17,%18,%19,%20,%21,%22,%23,%24,%25,%26,%27,%28,%29,%30,%31,%32,%33,%34,%35}, %36, %37, p, 1, 1, 0, 1;\n}\n"
    : "+f"(d[0]),"+f"(d[1]),"+f"(d[2]),"+f"(d[3]),"+f"(d[4]),"+f"(d[5]),"+f"(d[6]),"+f"(d[7]),"+f"(d[8]),"+f"(d[9]),"+f"(d[10]),"+f"(d[11]),"+f"(d[12]),"+f"(d[13]),"+f"(d[14]),"+f"(d[15]),"+f"(d[16]),"+f"(d[17]),"+f"(d[18]),"+f"(d[19]),"+f"(d[20]),"+f"(d[21]),"+f"(d[22]),"+f"(d[23]),"+f"(d[24]),"+f"(d[25]),"+f"(d[26]),"+f"(d[27]),"+f"(d[28]),"+f"(d[29]),"+f"(d[30]),"+f"(d[31]),"+f"(d[32]),"+f"(d[33]),"+f"(d[34]),"+f"(d[35])
    : "l"(da),"l"(db),"r"(sd));
}
__device__ __forceinline__ void wgmma_n64_k(float (&d)[32], uint32_t a0, uint32_t a1, uint32_t a2, uint32_t a3, uint64_t db, int sd) {
  asm volatile("{\n.reg .pred p;\nsetp.ne.b32 p, %37, 0;\n"
    "wgmma.mma_async.sync.aligned.m64n64k16.f32.bf16.bf16 "
    "{%0,%1,%2,%3,%4,%5,%6,%7,%8,%9,%10,%11,%12,%13,%14,%15,%16,%17,%18,%19,%20,%21,%22,%23,%24,%25,%26,%27,%28,%29,%30,%31}, {%32,%33,%34,%35}, %36, p, 1, 1, 0;\n}\n"
    : "+f"(d[0]),"+f"(d[1]),"+f"(d[2]),"+f"(d[3]),"+f"(d[4]),"+f"(d[5]),"+f"(d[6]),"+f"(d[7]),"+f"(d[8]),"+f"(d[9]),"+f"(d[10]),"+f"(d[11]),"+f"(d[12]),"+f"(d[13]),"+f"(d[14]),"+f"(d[15]),"+f"(d[16]),"+f"(d[17]),"+f"(d[18]),"+f"(d[19]),"+f"(d[20]),"+f"(d[21]),"+f"(d[22]),"+f"(d[23]),"+f"(d[24]),"+f"(d[25]),"+f"(d[26]),"+f"(d[27]),"+f"(d[28]),"+f"(d[29]),"+f"(d[30]),"+f"(d[31])
    : "r"(a0),"r"(a1),"r"(a2),"r"(a3),"l"(db),"r"(sd));
}
__device__ __forceinline__ void wgmma_n64_k(float (&d)[32], uint64_t da, uint64_t db, int sd) {
  asm volatile("{\n.reg .pred p;\nsetp.ne.b32 p, %34, 0;\n"
    "wgmma.mma_async.sync.aligned.m64n64k16.f32.bf16.bf16 "
    "{%0,%1,%2,%3,%4,%5,%6,%7,%8,%9,%10,%11,%12,%13,%14,%15,%16,%17,%18,%19,%20,%21,%22,%23,%24,%25,%26,%27,%28,%29,%30,%31}, %32, %33, p, 1, 1, 0, 0;\n}\n"
    : "+f"(d[0]),"+f"(d[1]),"+f"(d[2]),"+f"(d[3]),"+f"(d[4]),"+f"(d[5]),"+f"(d[6]),"+f"(d[7]),"+f"(d[8]),"+f"(d[9]),"+f"(d[10]),"+f"(d[11]),"+f"(d[12]),"+f"(d[13]),"+f"(d[14]),"+f"(d[15]),"+f"(d[16]),"+f"(d[17]),"+f"(d[18]),"+f"(d[19]),"+f"(d[20]),"+f"(d[21]),"+f"(d[22]),"+f"(d[23]),"+f"(d[24]),"+f"(d[25]),"+f"(d[26]),"+f"(d[27]),"+f"(d[28]),"+f"(d[29]),"+f"(d[30]),"+f"(d[31])
    : "l"(da),"l"(db),"r"(sd));
}

template <int N> __device__ __forceinline__ void fence_regs(float (&s)[N]) {
#pragma unroll
  for (int i = 0; i < N; i++) asm volatile("" : "+f"(s[i])::"memory");
}
template <int N> __device__ __forceinline__ void fence_regs(uint32_t (&s)[N]) {
#pragma unroll
  for (int i = 0; i < N; i++) asm volatile("" : "+r"(s[i])::"memory");
}
__device__ __forceinline__ float ex2(float x) { float r; asm("ex2.approx.ftz.f32 %0, %1;" : "=f"(r) : "f"(x)); return r; }
__device__ __forceinline__ uint32_t pack_bf16(float lo, float hi) { uint32_t r; asm("cvt.rn.bf16x2.f32 %0, %1, %2;" : "=r"(r) : "f"(hi), "f"(lo)); return r; }
__device__ __forceinline__ float bf_lo(uint32_t v) { return __uint_as_float(v << 16); }
__device__ __forceinline__ float bf_hi(uint32_t v) { return __uint_as_float(v & 0xFFFF0000u); }
__device__ __forceinline__ float rbf(float x) { return __bfloat162float(__float2bfloat16_rn(x)); }
__device__ __forceinline__ uint32_t hfma2(uint32_t a, uint32_t b, uint32_t c) { uint32_t r; asm("fma.rn.bf16x2 %0, %1, %2, %3;" : "=r"(r) : "r"(a), "r"(b), "r"(c)); return r; }
template <int LUT> __device__ __forceinline__ uint32_t lop3(uint32_t a, uint32_t b, uint32_t c) { uint32_t r; asm("lop3.b32 %0, %1, %2, %3, %4;" : "=r"(r) : "r"(a), "r"(b), "r"(c), "n"(LUT)); return r; }
__device__ __forceinline__ float sigmoidf_(float x) { return 1.f / (1.f + __expf(-x)); }
__device__ __forceinline__ void bar_sync(int id, int n) { asm volatile("bar.sync %0, %1;" ::"r"(id), "r"(n) : "memory"); }
__device__ __forceinline__ void fence_async() { asm volatile("fence.proxy.async.shared::cta;" ::: "memory"); }
__device__ __forceinline__ void fence_async_g() { asm volatile("fence.proxy.async.global;" ::: "memory"); }
__device__ __forceinline__ void cp_async16(uint32_t dst, const void* src) { asm volatile("cp.async.cg.shared.global [%0], [%1], 16;" ::"r"(dst), "l"(src) : "memory"); }
__device__ __forceinline__ void cp_async_wait_all() { asm volatile("cp.async.wait_all;" ::: "memory"); }
__device__ __forceinline__ uint4 ldg_nc(const void* p) { uint4 v; asm volatile("ld.global.nc.L1::no_allocate.v4.u32 {%0,%1,%2,%3}, [%4];" : "=r"(v.x), "=r"(v.y), "=r"(v.z), "=r"(v.w) : "l"(p)); return v; }
__device__ __forceinline__ uint2 ldg_nc2(const void* p) { uint2 v; asm volatile("ld.global.nc.L1::no_allocate.v2.u32 {%0,%1}, [%2];" : "=r"(v.x), "=r"(v.y) : "l"(p)); return v; }
__device__ __forceinline__ uint4 ldg_cg(const void* p) { uint4 v; asm volatile("ld.global.cg.v4.u32 {%0,%1,%2,%3}, [%4];" : "=r"(v.x), "=r"(v.y), "=r"(v.z), "=r"(v.w) : "l"(p) : "memory"); return v; }
__device__ __forceinline__ void prefetch_l2(const void* p, uint32_t bytes) { asm volatile("cp.async.bulk.prefetch.L2.global [%0], %1;" ::"l"(p), "r"(bytes) : "memory"); }

__device__ __forceinline__ int fresh_tid() { int t; asm volatile("mov.u32 %0, %%tid.x;" : "=r"(t)); return t; }
__device__ __forceinline__ int fresh_bid() { int t; asm volatile("mov.u32 %0, %%ctaid.x;" : "=r"(t)); return t; }
#define IDS                                                                                                          \
  const int tid = fresh_tid(), wg = tid >> 7, wi = (tid >> 5) & 3, lane = tid & 31, g = lane >> 2, c = lane & 3;     \
  const int bid = fresh_bid(), tb = bid >> 3, hg = bid & 7, mh = wg & 1, kh = wg >> 1, t128 = tid & 127;             \
  const int lrow = mh * 64 + wi * 16 + g;                                                                            \
  (void)wi; (void)g; (void)c; (void)tb; (void)hg; (void)mh; (void)kh; (void)t128; (void)lrow; (void)lane;
__device__ __forceinline__ unsigned ticket_arrive(unsigned* ctr, unsigned n) {
  unsigned old;
  asm volatile("atom.add.release.gpu.global.u32 %0, [%1], 1;" : "=r"(old) : "l"(ctr) : "memory");
  return (old / n + 1) * n;
}
__device__ __forceinline__ void ticket_wait(unsigned* ctr, unsigned target) {
  for (int it = 0; it < (1 << 22); it++) {
    unsigned v;
    asm volatile("ld.acquire.gpu.global.u32 %0, [%1];" : "=r"(v) : "l"(ctr) : "memory");
    if ((int)(v - target) >= 0) break;
  }
}
__device__ __forceinline__ void mbar_wait(uint32_t bar, uint32_t parity) {
  for (int it = 0; it < (1 << 20); it++) {
    uint32_t ok;
    asm volatile("{\n.reg .pred p;\nmbarrier.try_wait.parity.shared::cta.b64 p, [%1], %2;\nselp.u32 %0, 1, 0, p;\n}\n" : "=r"(ok) : "r"(bar), "r"(parity) : "memory");
    if (ok) break;
  }
}

struct PC { uint32_t msk, cb; };
__device__ __forceinline__ uint32_t exp2_sw(float u0, float u1, const PC& pc) {
  uint32_t w = __byte_perm(__float_as_uint(u0), __float_as_uint(u1), 0x6521);
  uint32_t g = lop3<0xEC>(w, 0x3F803F80u, pc.msk);
  uint32_t gp = lop3<0xCE>(w, 0xBF80BF80u, pc.msk);
  uint32_t t = hfma2(g, gp, 0x3FFF3FFFu);
  uint32_t q = hfma2(g, pc.cb, 0x3E4E3E4Eu);
  uint32_t m = hfma2(t, q, g);
  return lop3<0xD8>(w, m, pc.msk);
}
template <int HALF> __device__ __forceinline__ void softmax_half(const float (&s)[32], uint32_t (&p)[8], const PC& pc) {
#pragma unroll
  for (int i = 0; i < 4; i++) {
    const int b = HALF * 4 + i;
    if ((PMASK >> b) & 1) {
      p[2 * i] = exp2_sw(s[4 * b], s[4 * b + 1], pc);
      p[2 * i + 1] = exp2_sw(s[4 * b + 2], s[4 * b + 3], pc);
    } else {
      p[2 * i] = pack_bf16(ex2(s[4 * b]), ex2(s[4 * b + 1]));
      p[2 * i + 1] = pack_bf16(ex2(s[4 * b + 2]), ex2(s[4 * b + 3]));
    }
  }
}
__device__ __forceinline__ uint32_t tile_off(int t) { return (uint32_t)((t >> 2) * 1536 + (t & 3) * 192); }

__device__ __forceinline__ void qk(float (&s)[32], const uint32_t (&q)[8], uint64_t kd0, uint64_t kd1, uint32_t off) {
  wgmma_n64_k(s, q[0], q[1], q[2], q[3], kd0 + off, 0);
  wgmma_n64_k(s, q[4], q[5], q[6], q[7], kd1 + off, 1);
}
__device__ __forceinline__ void pv(float (&o)[12], const uint32_t (&p)[16], uint64_t vd, uint32_t off) {
#pragma unroll
  for (int k = 0; k < 4; k++) wgmma_n24_t(o, p[4 * k], p[4 * k + 1], p[4 * k + 2], p[4 * k + 3], vd + off + k * 48, 1);
}

__device__ __forceinline__ void pv_half(float (&o)[12], const uint32_t (&p)[8], uint64_t vd, uint32_t off) {
  wgmma_n24_t(o, p[0], p[1], p[2], p[3], vd + off, 1);
  wgmma_n24_t(o, p[4], p[5], p[6], p[7], vd + off + 48, 1);
}
__device__ __forceinline__ void attn_step(float (&sc)[32], float (&sn)[32], uint32_t (&pl)[8], uint32_t (&ph)[8], float (&o)[12],
                                          const uint32_t (&q)[8], uint64_t kd0, uint64_t kd1, uint64_t vd, uint32_t offc, uint32_t offn, const PC& pc) {
  wg_fence();
  qk(sn, q, kd0, kd1, offn);
  wg_commit();
  wg_wait<2>();
  fence_regs(pl);
  softmax_half<0>(sc, pl, pc);
  fence_regs(pl);
  wg_fence();
  pv_half(o, pl, vd, offc);
  wg_commit();
  wg_wait<2>();
  fence_regs(ph);
  softmax_half<1>(sc, ph, pc);
  fence_regs(ph);
  wg_fence();
  pv_half(o, ph, vd, offc + 96);
  wg_commit();
  wg_wait<2>();
  fence_regs(sn);
}
__device__ __forceinline__ void attn_fast(const uint32_t (&q)[8], float (&o)[12], uint32_t sb, const PC& pc) {
  const uint64_t kd0 = make_desc(sb, 128, 384), kd1 = make_desc(sb + 256, 0, 384), vd = make_desc(sb + 12288, 384, 128);
  float sA[32], sB[32];
  uint32_t pl[8], ph[8];
#pragma unroll
  for (int i = 0; i < 12; i++) o[i] = 0.f;
#pragma unroll
  for (int i = 0; i < 8; i++) { pl[i] = 0u; ph[i] = 0u; }
#pragma unroll
  for (int i = 0; i < 32; i++) { sA[i] = 0.f; sB[i] = 0.f; }
  mbar_wait(sb + SM_MBAR, 0);
  wg_fence();
  qk(sA, q, kd0, kd1, 0);
  wg_commit();
  wg_wait<0>();
  fence_regs(sA);
#pragma unroll 1
  for (int t = 0; t < 32; t += 2) {
    const uint32_t off = tile_off(t);
    attn_step(sA, sB, pl, ph, o, q, kd0, kd1, vd, off, off + 192, pc);
    const int t2 = (t + 2) & 31;
    if ((t2 & 3) == 0) mbar_wait(sb + SM_MBAR + (t2 >> 2) * 8, 0);
    attn_step(sB, sA, pl, ph, o, q, kd0, kd1, vd, off + 192, tile_off(t2), pc);
  }
  wg_wait<0>();
  fence_regs(o); fence_regs(pl); fence_regs(ph); fence_regs(sA);
}

__device__ __forceinline__ void attn_safe(const uint32_t (&q)[8], float (&o)[12], uint32_t sb) {
  const uint64_t kd0 = make_desc(sb, 128, 384), kd1 = make_desc(sb + 256, 0, 384), vd = make_desc(sb + 12288, 384, 128);
  float s[32];
  uint32_t p[16];
  float m0 = -INFINITY, m1 = -INFINITY;
#pragma unroll
  for (int i = 0; i < 32; i++) s[i] = 0.f;
#pragma unroll
  for (int i = 0; i < 12; i++) o[i] = 0.f;
#pragma unroll 1
  for (int t = 0; t < 32; t++) {
    if ((t & 3) == 0) mbar_wait(sb + SM_MBAR + (t >> 2) * 8, 0);
    wg_fence();
    qk(s, q, kd0, kd1, tile_off(t));
    wg_commit();
    wg_wait<0>();
    fence_regs(s);
#pragma unroll
    for (int b = 0; b < 8; b++) {
      const float sc = ((PMASK >> b) & 1) ? 0.5f : 1.f;
      m0 = fmaxf(m0, sc * fmaxf(s[4 * b], s[4 * b + 1]));
      m1 = fmaxf(m1, sc * fmaxf(s[4 * b + 2], s[4 * b + 3]));
    }
  }
  m0 = fmaxf(m0, __shfl_xor_sync(~0u, m0, 1)); m0 = fmaxf(m0, __shfl_xor_sync(~0u, m0, 2));
  m1 = fmaxf(m1, __shfl_xor_sync(~0u, m1, 1)); m1 = fmaxf(m1, __shfl_xor_sync(~0u, m1, 2));
#pragma unroll 1
  for (int t = 0; t < 32; t++) {
    wg_fence();
    qk(s, q, kd0, kd1, tile_off(t));
    wg_commit();
    wg_wait<0>();
    fence_regs(s);
#pragma unroll
    for (int b = 0; b < 8; b++) {
      const float sc = ((PMASK >> b) & 1) ? 0.5f : 1.f;
      p[2 * b] = pack_bf16(ex2(fmaf(s[4 * b], sc, -m0)), ex2(fmaf(s[4 * b + 1], sc, -m0)));
      p[2 * b + 1] = pack_bf16(ex2(fmaf(s[4 * b + 2], sc, -m1)), ex2(fmaf(s[4 * b + 3], sc, -m1)));
    }
    fence_regs(p);
    wg_fence();
    pv(o, p, vd, tile_off(t));
    wg_commit();
    wg_wait<0>();
    fence_regs(o); fence_regs(p);
  }
}

__device__ __forceinline__ int b_slot(int k, int gstride) {
  const int kl = k >= 288 ? k - 288 : k;
  const int kg = kl < 160 ? (k >> 3) : (k >> 5) * 4 + (k & 2) + ((k >> 2) & 1);
  const int r = kl < 160 ? (k & 7) : ((k >> 3) & 3) * 2 + (k & 1);
  return kg * gstride + r * 16;
}
__device__ __forceinline__ void stage_w(uint32_t sb, const __nv_bfloat16* w, int hg, int tid) {
#pragma unroll
  for (int i = 0; i < 11; i++) {
    int idx = tid + 512 * i;
    if (idx < 5184) {
      int k = idx / 9, nb = idx - k * 9;
      cp_async16(sb + SM_W + b_slot(k, 1296) + nb * 144, w + k * DM + hg * 72 + nb * 8);
    }
  }
}
template <bool CG> __device__ __forceinline__ void load_a(uint32_t (&xa)[32], const __nv_bfloat16* a, uint32_t sa, int t128) {
  const __nv_bfloat16* p = a + (size_t)((t128 >> 5) * 16 + ((t128 & 31) >> 2)) * DM + 160 + (t128 & 3) * 8;
#pragma unroll
  for (int j = 0; j < 4; j++) {
    uint4 r0 = CG ? ldg_cg(p + j * 32) : ldg_nc(p + j * 32), r1 = CG ? ldg_cg(p + 8 * DM + j * 32) : ldg_nc(p + 8 * DM + j * 32);
    xa[8 * j] = r0.x; xa[8 * j + 1] = r1.x; xa[8 * j + 2] = r0.z; xa[8 * j + 3] = r1.z;
    xa[8 * j + 4] = r0.y; xa[8 * j + 5] = r1.y; xa[8 * j + 6] = r0.w; xa[8 * j + 7] = r1.w;
  }
#pragma unroll
  for (int i = 0; i < 10; i++) {
    const int row = (t128 >> 2) + (i & 1) * 32, ch = (i >> 1) * 4 + (t128 & 3);
    cp_async16(sa + (row >> 3) * 2880 + ch * 144 + (row & 7) * 16, a + (size_t)row * DM + ch * 8);
  }
}
template <int NR> __device__ __forceinline__ void gemm288(float (&acc)[NR], const uint32_t (&xa)[32], uint32_t sa, uint64_t wd, int wstep) {
  const uint64_t ad = make_desc(sa, 144, 2880);
#pragma unroll
  for (int j = 0; j < NR; j++) acc[j] = 0.f;
  wg_fence();
#pragma unroll
  for (int j = 0; j < 10; j++) wgmma_t(acc, ad + (uint64_t)(j * 18), wd + (uint64_t)(j * wstep), j > 0);
#pragma unroll
  for (int j = 0; j < 8; j++) wgmma_t(acc, xa[4 * j], xa[4 * j + 1], xa[4 * j + 2], xa[4 * j + 3], wd + (uint64_t)((10 + j) * wstep), 1);
  wg_commit();
  wg_wait<0>();
  fence_regs(acc);
}
__device__ __forceinline__ void ksplit_reduce(float (&res)[20], const float (&acc)[36], uint8_t* smem, int wg, int t128, int rs) {
  float* mine = (float*)(smem + wg * rs) + t128;
  const float* other = (const float*)(smem + (wg ^ 2) * rs) + t128;
  const bool hi = wg >= 2;
#pragma unroll
  for (int i = 0; i < 20; i++) mine[i * 128] = hi ? acc[i] : acc[i < 16 ? 20 + i : 0];
  bar_sync(1 + (wg & 1), 256);
#pragma unroll
  for (int i = 0; i < 20; i++) res[i] = (hi ? acc[i < 16 ? 20 + i : 0] : acc[i]) + other[i * 128];
}

__global__ void __launch_bounds__(512, 1)
fused_kernel(const __nv_bfloat16* __restrict__ x, const __nv_bfloat16* __restrict__ wq, const __nv_bfloat16* __restrict__ wk,
             const __nv_bfloat16* __restrict__ wv, const __nv_bfloat16* __restrict__ wo, const __nv_bfloat16* __restrict__ w_r,
             const __nv_bfloat16* __restrict__ w_gate, const __nv_bfloat16* __restrict__ w_up, const __nv_bfloat16* __restrict__ w_down,
             const __nv_bfloat16* __restrict__ gate_w, __nv_bfloat16* __restrict__ out, uint32_t zero) {
  extern __shared__ __align__(1024) uint8_t smem[];
  const uint32_t sb = (uint32_t)__cvta_generic_to_shared(smem);
  {
  IDS
  unsigned tgt_kv = 0;

  if (tid == 0) {
#pragma unroll
    for (int i = 0; i < 8; i++) asm volatile("mbarrier.init.shared::cta.b64 [%0], 1;" ::"r"(sb + SM_MBAR + i * 8) : "memory");
    if (hg >= 6) tgt_kv = ticket_arrive(&g_ctr[0], NCTA);
  }
  uint32_t xa[32];
  {
    uint4 ev[2];
    if (hg < 6) {
#pragma unroll
      for (int i = 0; i < 2; i++) {
        int k = tid + 512 * i;
        ev[i] = make_uint4(0, 0, 0, 0);
        if (k < DM) {
          const uint32_t* src = (const uint32_t*)((hg < 3 ? wk : wv) + k * 18) + (hg % 3) * 4;
          ev[i].x = __ldg(src);
          if (hg % 3 != 2) { ev[i].y = __ldg(src + 1); ev[i].z = __ldg(src + 2); ev[i].w = __ldg(src + 3); }
          else if (hg == 2) ev[i].y = (uint32_t)__bfloat16_as_ushort(w_r[k]) | ((uint32_t)__bfloat16_as_ushort(gate_w[k]) << 16);
        }
      }
    }
    load_a<false>(xa, x + (size_t)(tb * 128 + mh * 64) * DM + kh * 288, sb + wg * 23040, t128);
    asm volatile("cp.async.commit_group;" ::: "memory");
    stage_w(sb, wq, hg, tid);
    asm volatile("cp.async.commit_group;" ::: "memory");
    if (hg < 6) {
#pragma unroll
      for (int i = 0; i < 2; i++) {
        int k = tid + 512 * i;
        if (k < DM) *(uint4*)(smem + SM_EXT + b_slot(k, 128)) = ev[i];
      }
    }
  }
  asm volatile("cp.async.wait_group 1;" ::: "memory");
  fence_async();
  __syncthreads();
  if (hg < 6) {
    float e[4];
    gemm288(e, xa, sb + wg * 23040, make_desc(sb + SM_EXT + kh * 36 * 128, 128, 128), 16);
    float4* er = (float4*)(smem + SM_ERED) + mh * 128 + t128;
    if (kh == 1) *er = make_float4(e[0], e[1], e[2], e[3]);
    bar_sync(1 + mh, 256);
    if (kh == 0) {
      float4 o4 = *er;
      e[0] += o4.x; e[1] += o4.y; e[2] += o4.z; e[3] += o4.w;
      const int ch = hg % 3;
      float nrm = 0.f;
      unsigned long long best = 0ull;
#pragma unroll
      for (int h = 0; h < 2; h++) {
        const int key = tb * 128 + lrow + 8 * h;
        const bool poly = (PMASK >> ((key >> 3) & 7)) & 1;
        uint32_t v = pack_bf16(e[2 * h], e[2 * h + 1]);
        if (hg < 3) {
          float lo = bf_lo(v), hi = bf_hi(v);
          float n2 = (hg == 2 && c != 0) ? 0.f : lo * lo + hi * hi;
          n2 += __shfl_xor_sync(~0u, n2, 1);
          n2 += __shfl_xor_sync(~0u, n2, 2);
          nrm = fmaxf(nrm, n2);
          if (hg == 2 && c == 1) {
            g_gate[key] = rbf(sigmoidf_(hi));
            uint32_t rb = __float_as_uint(lo);
            rb = (rb & 0x80000000u) ? ~rb : (rb | 0x80000000u);
            unsigned long long cand = ((unsigned long long)rb << 32) | (uint32_t)(~key);
            best = cand > best ? cand : best;
          }
          if (poly) v = pack_bf16(2.f * lo, 2.f * hi);
          if (hg == 2 && c != 0) v = c == 1 ? (poly ? 0x44404000u : 0x00003F80u) : (c == 2 && poly ? 0x0000BFFFu : 0u);
        } else if (hg == 5 && c != 0) {
          v = c == 1 ? 0x00003F80u : 0u;
        }
        uint8_t* dst = (uint8_t*)g_kv + (key >> 8) * 24576 + (hg >= 3 ? 12288 : 0) + ((key >> 3) & 31) * 384 + ch * 128 + (key & 7) * 16 + c * 4;
        *(uint32_t*)dst = v;
      }
      if (hg < 3) {
#pragma unroll
        for (int o = 4; o < 32; o <<= 1) nrm = fmaxf(nrm, __shfl_xor_sync(~0u, nrm, o));
        if (lane == 0) ((float*)&g_kn[tb * 8 + mh * 4 + wi])[hg] = nrm;
        if (hg == 2) {
#pragma unroll
          for (int o = 1; o < 32; o <<= 1) { unsigned long long b2 = __shfl_xor_sync(~0u, best, o); best = b2 > best ? b2 : best; }
          if (lane == 0) g_best[tb * 8 + mh * 4 + wi] = best;
        }
      }
      fence_async_g();
      bar_sync(3, 256);
      if (tid == 0) tgt_kv = ticket_arrive(&g_ctr[0], NCTA);
    }
  }
  cp_async_wait_all();
  fence_async();
  __syncthreads();
  {
    float acc0[36], acc[20];
    gemm288(acc0, xa, sb + wg * 23040, make_desc(sb + SM_W + kh * 36 * 1296, 1296, 144), 162);
    ksplit_reduce(acc, acc0, smem, wg, t128, 23040);
    const float qs = 0.23570226039551584f * 1.4426950408889634f;
    uint8_t* qp = smem + SM_Q + lrow * 144 + kh * 80 + c * 4;
#pragma unroll
    for (int nb = 0; nb < 5; nb++) {
      if (nb < 4 || kh == 0) {
        *(uint32_t*)(qp + nb * 16) = pack_bf16(acc[4 * nb] * qs, acc[4 * nb + 1] * qs);
        *(uint32_t*)(qp + 8 * 144 + nb * 16) = pack_bf16(acc[4 * nb + 2] * qs, acc[4 * nb + 3] * qs);
      }
    }
  }
  fence_async();
  __syncthreads();
  if (tid == 0) {
    ticket_wait(&g_ctr[0], tgt_kv);
    fence_async_g();
#pragma unroll
    for (int i = 0; i < 8; i++) {
      asm volatile("mbarrier.arrive.expect_tx.shared::cta.b64 _, [%0], 24576;" ::"r"(sb + SM_MBAR + i * 8) : "memory");
      asm volatile("cp.async.bulk.shared::cluster.global.mbarrier::complete_tx::bytes [%0], [%1], 24576, [%2];"
                   ::"r"(sb + i * 24576), "l"((const uint8_t*)g_kv + i * 24576), "r"(sb + SM_MBAR + i * 8) : "memory");
    }
    prefetch_l2((const uint8_t*)wo + bid * 5184, 5184);
    prefetch_l2((const uint8_t*)w_gate + bid * 41472, 41472);
    prefetch_l2((const uint8_t*)w_up + bid * 41472, 41472);
    prefetch_l2((const uint8_t*)w_down + bid * 41472, 41472);
  }
  __syncthreads();
  {
    float kmax = 0.f;
#pragma unroll
    for (int i = 0; i < 4; i++) { float4 v = g_kn[lane + 32 * i]; kmax = fmaxf(kmax, v.x + v.y + v.z); }
#pragma unroll
    for (int o = 1; o < 32; o <<= 1) kmax = fmaxf(kmax, __shfl_xor_sync(~0u, kmax, o));
    if (lane == 0) *(volatile float*)(smem + SM_MISC + 512 + (tid >> 5) * 4) = kmax;
    __syncwarp();
  }
  }
  {
    PC pc; pc.msk = 0x007F007Fu + zero; pc.cb = 0x3DCD3DCDu + zero;
#pragma unroll 1
    for (int pass = 0; pass < 2; pass++) {
      uint32_t q[8];
      uint32_t unsafe;
      {
      IDS
      const float kmax = *(volatile float*)(smem + SM_MISC + 512 + (tid >> 5) * 4);
      const int r0 = pass * 64 + wi * 16 + g;
      const uint8_t* qp = smem + SM_Q + r0 * 144 + wg * 36 + c * 4;
      q[0] = *(const uint32_t*)qp; q[1] = *(const uint32_t*)(qp + 8 * 144);
      q[2] = *(const uint32_t*)(qp + 16); q[3] = *(const uint32_t*)(qp + 8 * 144 + 16);
      q[4] = c == 0 ? *(const uint32_t*)(qp + 32) : 0u; q[5] = c == 0 ? *(const uint32_t*)(qp + 8 * 144 + 32) : 0u;
      float n0 = bf_lo(q[0]) * bf_lo(q[0]) + bf_hi(q[0]) * bf_hi(q[0]) + bf_lo(q[2]) * bf_lo(q[2]) + bf_hi(q[2]) * bf_hi(q[2]) + bf_lo(q[4]) * bf_lo(q[4]) + bf_hi(q[4]) * bf_hi(q[4]);
      float n1 = bf_lo(q[1]) * bf_lo(q[1]) + bf_hi(q[1]) * bf_hi(q[1]) + bf_lo(q[3]) * bf_lo(q[3]) + bf_hi(q[3]) * bf_hi(q[3]) + bf_lo(q[5]) * bf_lo(q[5]) + bf_hi(q[5]) * bf_hi(q[5]);
      n0 += __shfl_xor_sync(~0u, n0, 1); n0 += __shfl_xor_sync(~0u, n0, 2);
      n1 += __shfl_xor_sync(~0u, n1, 1); n1 += __shfl_xor_sync(~0u, n1, 2);
      const float m0 = ceilf(sqrtf(n0 * kmax) * 1.001f + 0.01f), m1 = ceilf(sqrtf(n1 * kmax) * 1.001f + 0.01f);
      asm volatile("{\n.reg .pred p, r;\nsetp.ne.u32 p, %1, 0;\nbarrier.cta.red.or.pred.aligned r, %2, 128, p;\nselp.u32 %0, 1, 0, r;\n}\n"
                   : "=r"(unsafe) : "r"((uint32_t)!(m0 <= 60.f && m1 <= 60.f)), "r"(4 + wg) : "memory");
      q[6] = unsafe ? 0u : c == 1 ? pack_bf16(-m0, 1.f) : c == 2 ? 0x3F803F80u : 0u;
      q[7] = unsafe ? 0u : c == 1 ? pack_bf16(-m1, 1.f) : c == 2 ? 0x3F803F80u : 0u;
      }
      float o[12];
      if (!unsafe) {
        attn_fast(q, o, sb, pc);
      } else {
        attn_safe(q, o, sb);
      }
      IDS
      const float i0 = 1.f / __shfl_sync(~0u, o[8], (lane & ~3) | 1), i1 = 1.f / __shfl_sync(~0u, o[10], (lane & ~3) | 1);
      uint8_t* ob = (uint8_t*)g_o + tb * 147456 + (pass + 2 * (hg >> 2)) * 36864 + wi * 9216 + g * 16;
      const int c0 = (hg & 3) * 72 + wg * 18 + 2 * c;
      uint8_t* p0 = ob + (c0 >> 3) * 128 + (c0 & 7) * 2;
      *(uint32_t*)p0 = pack_bf16(o[0] * i0, o[1] * i0); *(uint32_t*)(p0 + 4608) = pack_bf16(o[2] * i1, o[3] * i1);
      *(uint32_t*)(p0 + 128) = pack_bf16(o[4] * i0, o[5] * i0); *(uint32_t*)(p0 + 4608 + 128) = pack_bf16(o[6] * i1, o[7] * i1);
      if (c == 0) { *(uint32_t*)(p0 + 256) = pack_bf16(o[8] * i0, o[9] * i0); *(uint32_t*)(p0 + 4608 + 256) = pack_bf16(o[10] * i1, o[11] * i1); }
    }
  }
  fence_async_g();
  __syncthreads();
  IDS
  unsigned tgt_o = 0, tgt_y = 0;
  if (tid == 0) tgt_o = ticket_arrive(&g_ctr[32 * (1 + tb)], 8);
#pragma unroll
  for (int i = 0; i < 11; i++) {
    const int idx = tid + 512 * i;
    if (idx < 5184) {
      const int kg = idx / 72, rem = idx - kg * 72;
      cp_async16(sb + SM_W3 + idx * 16, wo + (kg * 8 + (rem & 7)) * DM + hg * 72 + (rem >> 3) * 8);
    }
  }

  int sel;
  float rsel;
  {
    uint2 wgv[12], wuv[12];
    uint4 wdv[6];
    const int q9 = tid % 9, rg = tid / 9, c72 = tid % 72, r6 = tid / 72;
    if (tid < 432) {
#pragma unroll
      for (int i = 0; i < 12; i++) {
        size_t off = (size_t)(rg + 48 * i) * FF + bid * 36 + q9 * 4;
        wgv[i] = ldg_nc2(w_gate + off); wuv[i] = ldg_nc2(w_up + off);
      }
#pragma unroll
      for (int i = 0; i < 6; i++) wdv[i] = ldg_nc(w_down + (size_t)(bid * 36 + r6 * 6 + i) * DM + c72 * 8);
    }
    unsigned long long best = 0ull;
#pragma unroll
    for (int i = 0; i < 4; i++) { unsigned long long b2 = g_best[lane + 32 * i]; best = b2 > best ? b2 : best; }
#pragma unroll
    for (int o = 1; o < 32; o <<= 1) { unsigned long long b2 = __shfl_xor_sync(~0u, best, o); best = b2 > best ? b2 : best; }
    sel = (int)(~(uint32_t)best) & (S_LEN - 1);
    uint32_t rb = (uint32_t)(best >> 32);
    rb = (rb & 0x80000000u) ? (rb & 0x7FFFFFFFu) : ~rb;
    rsel = rbf(sigmoidf_(__uint_as_float(rb)));
    float* m1 = (float*)(smem + SM_MOE1);
    float* m2 = (float*)(smem + SM_MOE2);
    float* hs = (float*)(smem + SM_MISC);
    if (tid < 432) {
      float ga[4] = {0.f, 0.f, 0.f, 0.f}, ua[4] = {0.f, 0.f, 0.f, 0.f};
#pragma unroll
      for (int i = 0; i < 12; i++) {
        float xv = __bfloat162float(x[(size_t)sel * DM + rg + 48 * i]);
        ga[0] = fmaf(xv, bf_lo(wgv[i].x), ga[0]); ga[1] = fmaf(xv, bf_hi(wgv[i].x), ga[1]);
        ga[2] = fmaf(xv, bf_lo(wgv[i].y), ga[2]); ga[3] = fmaf(xv, bf_hi(wgv[i].y), ga[3]);
        ua[0] = fmaf(xv, bf_lo(wuv[i].x), ua[0]); ua[1] = fmaf(xv, bf_hi(wuv[i].x), ua[1]);
        ua[2] = fmaf(xv, bf_lo(wuv[i].y), ua[2]); ua[3] = fmaf(xv, bf_hi(wuv[i].y), ua[3]);
      }
      *(float4*)(m1 + rg * 72 + q9 * 4) = make_float4(ga[0], ga[1], ga[2], ga[3]);
      *(float4*)(m1 + rg * 72 + 36 + q9 * 4) = make_float4(ua[0], ua[1], ua[2], ua[3]);
    }
    __syncthreads();
    if (tid < 432) {
      float s = 0.f;
#pragma unroll
      for (int i = 0; i < 8; i++) s += m1[(r6 * 8 + i) * 72 + c72];
      m2[r6 * 72 + c72] = s;
    }
    __syncthreads();
    if (tid < 36) {
      float gs = 0.f, us = 0.f;
#pragma unroll
      for (int i = 0; i < 6; i++) { gs += m2[i * 72 + tid]; us += m2[i * 72 + 36 + tid]; }
      gs = rbf(gs); us = rbf(us);
      hs[tid] = rbf(rbf(gs * sigmoidf_(gs)) * us);
    }
    __syncthreads();
    if (tid < 432) {
      float y[8] = {0.f, 0.f, 0.f, 0.f, 0.f, 0.f, 0.f, 0.f};
#pragma unroll
      for (int i = 0; i < 6; i++) {
        float hv = hs[r6 * 6 + i];
        y[0] = fmaf(hv, bf_lo(wdv[i].x), y[0]); y[1] = fmaf(hv, bf_hi(wdv[i].x), y[1]);
        y[2] = fmaf(hv, bf_lo(wdv[i].y), y[2]); y[3] = fmaf(hv, bf_hi(wdv[i].y), y[3]);
        y[4] = fmaf(hv, bf_lo(wdv[i].z), y[4]); y[5] = fmaf(hv, bf_hi(wdv[i].z), y[5]);
        y[6] = fmaf(hv, bf_lo(wdv[i].w), y[6]); y[7] = fmaf(hv, bf_hi(wdv[i].w), y[7]);
      }
      *(float4*)(m1 + r6 * DM + c72 * 8) = make_float4(y[0], y[1], y[2], y[3]);
      *(float4*)(m1 + r6 * DM + c72 * 8 + 4) = make_float4(y[4], y[5], y[6], y[7]);
    }
    __syncthreads();
    if (tid < 288) {
      float2 s = make_float2(0.f, 0.f);
#pragma unroll
      for (int i = 0; i < 6; i++) { float2 v = *(float2*)(m1 + i * DM + tid * 2); s.x += v.x; s.y += v.y; }
      *(float2*)(g_ypart + bid * DM + tid * 2) = s;
    }
    cp_async_wait_all();
    fence_async();
    __syncthreads();
    if (tid == 0) {
      tgt_y = ticket_arrive(&g_ctr[32 * 17], NCTA);
      ticket_wait(&g_ctr[32 * (1 + tb)], tgt_o);
      fence_async_g();
#pragma unroll
      for (int i = 0; i < 4; i++) {
        asm volatile("mbarrier.arrive.expect_tx.shared::cta.b64 _, [%0], 36864;" ::"r"(sb + SM_MBAR + i * 8) : "memory");
        asm volatile("cp.async.bulk.shared::cluster.global.mbarrier::complete_tx::bytes [%0], [%1], 36864, [%2];"
                     ::"r"(sb + i * 36864), "l"((const uint8_t*)g_o + tb * 147456 + i * 36864), "r"(sb + SM_MBAR + i * 8) : "memory");
      }
    }
  }

  {
    const int row = tb * 128 + lrow;
    const int nb0 = kh == 0 ? 0 : 5;
    uint32_t xr[10];
    {
      const uint32_t* xp = (const uint32_t*)(x + (size_t)row * DM + hg * 72 + nb0 * 8) + c;
#pragma unroll
      for (int i = 0; i < 5; i++) {
        xr[2 * i] = (i < 4 || kh == 0) ? __ldg(xp + i * 4) : 0u;
        xr[2 * i + 1] = (i < 4 || kh == 0) ? __ldg(xp + 4 * DM + i * 4) : 0u;
      }
    }
    const float g0 = g_gate[row], g1 = g_gate[row + 8];
    float acc0[36], acc[20];
    {
      const uint64_t ad = make_desc(sb + wg * 36864, 128, 4608), wd = make_desc(sb + SM_W3 + kh * 36 * 1152, 1152, 128);
#pragma unroll
      for (int j = 0; j < 36; j++) acc0[j] = 0.f;
      mbar_wait(sb + SM_MBAR + wg * 8, 1);
      wg_fence();
#pragma unroll
      for (int j = 0; j < 18; j++) wgmma_t(acc0, ad + (uint64_t)(j * 16), wd + (uint64_t)(j * 144), 1);
      wg_commit();
      wg_wait<0>();
      fence_regs(acc0);
    }
    ksplit_reduce(acc, acc0, smem, wg, t128, 36864);
    float* upd = (float*)(smem + SM_MISC);
    const bool owner = (sel >> 7) == tb;
    if (owner) {
      float* m2 = (float*)(smem + SM_W3);
      if (tid == 0) ticket_wait(&g_ctr[32 * 17], tgt_y);
      __syncthreads();
      if (tid < 288) {
        const int c72 = tid % 72, pt = tid / 72;
        float s = 0.f;
#pragma unroll 8
        for (int i = 0; i < 32; i++) s += __ldcg(g_ypart + (pt * 32 + i) * DM + hg * 72 + c72);
        m2[tid] = s;
      }
      __syncthreads();
      if (tid < 72) upd[tid] = rbf(rbf(m2[tid] + m2[72 + tid] + m2[144 + tid] + m2[216 + tid]) * rsel);
      __syncthreads();
    }
    const float h0 = rbf(1.f - g0), h1 = rbf(1.f - g1);
    uint32_t* op = (uint32_t*)(out + (size_t)row * DM + hg * 72 + nb0 * 8) + c;
#pragma unroll
    for (int i = 0; i < 5; i++) {
      if (i < 4 || kh == 0) {
        const float a0 = acc[4 * i], a1 = acc[4 * i + 1], a2 = acc[4 * i + 2], a3 = acc[4 * i + 3];
        const uint32_t x0 = xr[2 * i], x1 = xr[2 * i + 1];
        float b0 = bf_lo(x0), b1 = bf_hi(x0), b2 = bf_lo(x1), b3 = bf_hi(x1);
        if (owner) {
          const int col = (nb0 + i) * 8 + c * 2;
          if (row == sel) { b0 = rbf(b0 + upd[col]); b1 = rbf(b1 + upd[col + 1]); }
          if (row + 8 == sel) { b2 = rbf(b2 + upd[col]); b3 = rbf(b3 + upd[col + 1]); }
        }
        op[i * 4] = pack_bf16(rbf(g0 * rbf(a0)) + rbf(h0 * b0), rbf(g0 * rbf(a1)) + rbf(h0 * b1));
        op[4 * DM + i * 4] = pack_bf16(rbf(g1 * rbf(a2)) + rbf(h1 * b2), rbf(g1 * rbf(a3)) + rbf(h1 * b3));
      }
    }
  }
}

extern "C" void kernel_launch(void* const* d_in, const int* in_sizes, int n_in, void* d_out, int out_size) {
  cudaFuncSetAttribute(fused_kernel, cudaFuncAttributeMaxDynamicSharedMemorySize, SM_TOTAL);
  typedef const __nv_bfloat16* P;
  fused_kernel<<<NCTA, 512, SM_TOTAL, cudaStreamPerThread>>>((P)d_in[0], (P)d_in[1], (P)d_in[2], (P)d_in[3], (P)d_in[4], (P)d_in[6],
                                                            (P)d_in[7], (P)d_in[8], (P)d_in[9], (P)d_in[10], (__nv_bfloat16*)d_out, 0u);
}
```

```cpp
#include <cuda_runtime.h>
#include <cuda_bf16.h>
#include <stdint.h>

#define S_LEN 2048
#define DM 576
#define FF 4608
#define NCTA 128
#define PMASK 0xB5u

__device__ uint4 g_kv[8 * 1536];
__device__ float4 g_kn[128];
__device__ unsigned long long g_best[128];
__device__ float g_gate[S_LEN];
__device__ uint4 g_o[S_LEN * DM / 8];
__device__ float g_ypart[NCTA * DM];
__device__ unsigned g_ctr[32 * 32];

#define SM_W 98304
#define SM_W3 147456
#define SM_RED 0
#define SM_MOE1 40960
#define SM_MOE2 57344
#define SM_Q 196608
#define SM_EXT 215040
#define SM_XSEL 224256
#define SM_ERED 226560
#define SM_MBAR 230656
#define SM_MISC 230720
#define SM_TOTAL 231424

__device__ __forceinline__ uint64_t make_desc(uint32_t saddr, uint32_t lbo, uint32_t sbo) {
  return (uint64_t)((saddr & 0x3FFFF) >> 4) | ((uint64_t)(lbo >> 4) << 16) | ((uint64_t)(sbo >> 4) << 32);
}
__device__ __forceinline__ void wg_fence() { asm volatile("wgmma.fence.sync.aligned;" ::: "memory"); }
__device__ __forceinline__ void wg_commit() { asm volatile("wgmma.commit_group.sync.aligned;" ::: "memory"); }
template <int N> __device__ __forceinline__ void wg_wait() { asm volatile("wgmma.wait_group.sync.aligned %0;" ::"n"(N) : "memory"); }
__device__ __forceinline__ void wgmma_t(float (&d)[4], uint32_t a0, uint32_t a1, uint32_t a2, uint32_t a3, uint64_t db, int sd) {
  asm volatile("{\n.reg .pred p;\nsetp.ne.b32 p, %9, 0;\n"
    "wgmma.mma_async.sync.aligned.m64n8k16.f32.bf16.bf16 "
    "{%0,%1,%2,%3}, {%4,%5,%6,%7}, %8, p, 1, 1, 1;\n}\n"
    : "+f"(d[0]),"+f"(d[1]),"+f"(d[2]),"+f"(d[3])
    : "r"(a0),"r"(a1),"r"(a2),"r"(a3),"l"(db),"r"(sd));
}
__device__ __forceinline__ void wgmma_t(float (&d)[4], uint64_t da, uint64_t db, int sd) {
  asm volatile("{\n.reg .pred p;\nsetp.ne.b32 p, %6, 0;\n"
    "wgmma.mma_async.sync.aligned.m64n8k16.f32.bf16.bf16 "
    "{%0,%1,%2,%3}, %4, %5, p, 1, 1, 0, 1;\n}\n"
    : "+f"(d[0]),"+f"(d[1]),"+f"(d[2]),"+f"(d[3])
    : "l"(da),"l"(db),"r"(sd));
}
__device__ __forceinline__ void wgmma_t(float (&d)[36], uint32_t a0, uint32_t a1, uint32_t a2, uint32_t a3, uint64_t db, int sd) {
  asm volatile("{\n.reg .pred p;\nsetp.ne.b32 p, %41, 0;\n"
    "wgmma.mma_async.sync.aligned.m64n72k16.f32.bf16.bf16 "
    "{%0,%1,%2,%3,%4,%5,%6,%7,%8,%9,%10,%11,%12,%13,%14,%15,%16,%17,%18,%19,%20,%21,%22,%23,%24,%25,%26,%27,%28,%29,%30,%31,%32,%33,%34,%35}, {%36,%37,%38,%39}, %40, p, 1, 1, 1;\n}\n"
    : "+f"(d[0]),"+f"(d[1]),"+f"(d[2]),"+f"(d[3]),"+f"(d[4]),"+f"(d[5]),"+f"(d[6]),"+f"(d[7]),"+f"(d[8]),"+f"(d[9]),"+f"(d[10]),"+f"(d[11]),"+f"(d[12]),"+f"(d[13]),"+f"(d[14]),"+f"(d[15]),"+f"(d[16]),"+f"(d[17]),"+f"(d[18]),"+f"(d[19]),"+f"(d[20]),"+f"(d[21]),"+f"(d[22]),"+f"(d[23]),"+f"(d[24]),"+f"(d[25]),"+f"(d[26]),"+f"(d[27]),"+f"(d[28]),"+f"(d[29]),"+f"(d[30]),"+f"(d[31]),"+f"(d[32]),"+f"(d[33]),"+f"(d[34]),"+f"(d[35])
    : "r"(a0),"r"(a1),"r"(a2),"r"(a3),"l"(db),"r"(sd));
}
__device__ __forceinline__ void wgmma_t(float (&d)[36], uint64_t da, uint64_t db, int sd) {
  asm volatile("{\n.reg .pred p;\nsetp.ne.b32 p, %38, 0;\n"
    "wgmma.mma_async.sync.aligned.m64n72k16.f32.bf16.bf16 "
    "{%0,%1,%2,%3,%4,%5,%6,%7,%8,%9,%10,%11,%12,%13,%14,%15,%16,%17,%18,%19,%20,%21,%22,%23,%24,%25,%26,%27,%28,%29,%30,%31,%32,%33,%34,%35}, %36, %37, p, 1, 1, 0, 1;\n}\n"
    : "+f"(d[0]),"+f"(d[1]),"+f"(d[2]),"+f"(d[3]),"+f"(d[4]),"+f"(d[5]),"+f"(d[6]),"+f"(d[7]),"+f"(d[8]),"+f"(d[9]),"+f"(d[10]),"+f"(d[11]),"+f"(d[12]),"+f"(d[13]),"+f"(d[14]),"+f"(d[15]),"+f"(d[16]),"+f"(d[17]),"+f"(d[18]),"+f"(d[19]),"+f"(d[20]),"+f"(d[21]),"+f"(d[22]),"+f"(d[23]),"+f"(d[24]),"+f"(d[25]),"+f"(d[26]),"+f"(d[27]),"+f"(d[28]),"+f"(d[29]),"+f"(d[30]),"+f"(d[31]),"+f"(d[32]),"+f"(d[33]),"+f"(d[34]),"+f"(d[35])
    : "l"(da),"l"(db),"r"(sd));
}
template <int HI, int SD> __device__ __forceinline__ void wgmma_pv(float (&d)[12], uint32_t a0, uint32_t a1, uint32_t a2, uint32_t a3, uint32_t lo) {
  asm volatile("{\n.reg .pred p;\n.reg .b64 db;\nsetp.ne.b32 p, %18, 0;\nmov.b64 db, {%16, %17};\n"
    "wgmma.mma_async.sync.aligned.m64n24k16.f32.bf16.bf16 "
    "{%0,%1,%2,%3,%4,%5,%6,%7,%8,%9,%10,%11}, {%12,%13,%14,%15}, db, p, 1, 1, 1;\n}\n"
    : "+f"(d[0]),"+f"(d[1]),"+f"(d[2]),"+f"(d[3]),"+f"(d[4]),"+f"(d[5]),"+f"(d[6]),"+f"(d[7]),"+f"(d[8]),"+f"(d[9]),"+f"(d[10]),"+f"(d[11])
    : "r"(a0),"r"(a1),"r"(a2),"r"(a3),"r"(lo),"n"(HI),"n"(SD));
}
template <int HI, int SD> __device__ __forceinline__ void wgmma_qk(float (&d)[16], uint32_t a0, uint32_t a1, uint32_t a2, uint32_t a3, uint32_t lo) {
  asm volatile("{\n.reg .pred p;\n.reg .b64 db;\nsetp.ne.b32 p, %22, 0;\nmov.b64 db, {%20, %21};\n"
    "wgmma.mma_async.sync.aligned.m64n32k16.f32.bf16.bf16 "
    "{%0,%1,%2,%3,%4,%5,%6,%7,%8,%9,%10,%11,%12,%13,%14,%15}, {%16,%17,%18,%19}, db, p, 1, 1, 0;\n}\n"
    : "+f"(d[0]),"+f"(d[1]),"+f"(d[2]),"+f"(d[3]),"+f"(d[4]),"+f"(d[5]),"+f"(d[6]),"+f"(d[7]),"+f"(d[8]),"+f"(d[9]),"+f"(d[10]),"+f"(d[11]),"+f"(d[12]),"+f"(d[13]),"+f"(d[14]),"+f"(d[15])
    : "r"(a0),"r"(a1),"r"(a2),"r"(a3),"r"(lo),"n"(HI),"n"(SD));
}

template <int N> __device__ __forceinline__ void fence_regs(float (&s)[N]) {
#pragma unroll
  for (int i = 0; i < N; i++) asm volatile("" : "+f"(s[i])::"memory");
}
template <int N> __device__ __forceinline__ void fence_regs(uint32_t (&s)[N]) {
#pragma unroll
  for (int i = 0; i < N; i++) asm volatile("" : "+r"(s[i])::"memory");
}
__device__ __forceinline__ float ex2(float x) { float r; asm("ex2.approx.ftz.f32 %0, %1;" : "=f"(r) : "f"(x)); return r; }
__device__ __forceinline__ uint32_t pack_bf16(float lo, float hi) { uint32_t r; asm("cvt.rn.bf16x2.f32 %0, %1, %2;" : "=r"(r) : "f"(hi), "f"(lo)); return r; }
__device__ __forceinline__ float bf_lo(uint32_t v) { return __uint_as_float(v << 16); }
__device__ __forceinline__ float bf_hi(uint32_t v) { return __uint_as_float(v & 0xFFFF0000u); }
__device__ __forceinline__ float rbf(float x) { return __bfloat162float(__float2bfloat16_rn(x)); }
__device__ __forceinline__ uint32_t hfma2(uint32_t a, uint32_t b, uint32_t c) { uint32_t r; asm("fma.rn.bf16x2 %0, %1, %2, %3;" : "=r"(r) : "r"(a), "r"(b), "r"(c)); return r; }
template <int LUT> __device__ __forceinline__ uint32_t lop3(uint32_t a, uint32_t b, uint32_t c) { uint32_t r; asm("lop3.b32 %0, %1, %2, %3, %4;" : "=r"(r) : "r"(a), "r"(b), "r"(c), "n"(LUT)); return r; }
__device__ __forceinline__ float sigmoidf_(float x) { return 1.f / (1.f + __expf(-x)); }
__device__ __forceinline__ void bar_sync(int id, int n) { asm volatile("bar.sync %0, %1;" ::"r"(id), "r"(n) : "memory"); }
__device__ __forceinline__ void fence_async() { asm volatile("fence.proxy.async.shared::cta;" ::: "memory"); }
__device__ __forceinline__ void fence_async_g() { asm volatile("fence.proxy.async.global;" ::: "memory"); }
__device__ __forceinline__ void cp_async16(uint32_t dst, const void* src) { asm volatile("cp.async.cg.shared.global [%0], [%1], 16;" ::"r"(dst), "l"(src) : "memory"); }
__device__ __forceinline__ void cp_async_wait_all() { asm volatile("cp.async.wait_all;" ::: "memory"); }
__device__ __forceinline__ uint4 ldg_nc(const void* p) { uint4 v; asm volatile("ld.global.nc.L1::no_allocate.v4.u32 {%0,%1,%2,%3}, [%4];" : "=r"(v.x), "=r"(v.y), "=r"(v.z), "=r"(v.w) : "l"(p)); return v; }
__device__ __forceinline__ uint2 ldg_nc2(const void* p) { uint2 v; asm volatile("ld.global.nc.L1::no_allocate.v2.u32 {%0,%1}, [%2];" : "=r"(v.x), "=r"(v.y) : "l"(p)); return v; }
__device__ __forceinline__ uint4 ldg_cg(const void* p) { uint4 v; asm volatile("ld.global.cg.v4.u32 {%0,%1,%2,%3}, [%4];" : "=r"(v.x), "=r"(v.y), "=r"(v.z), "=r"(v.w) : "l"(p) : "memory"); return v; }
__device__ __forceinline__ void prefetch_l2(const void* p, uint32_t bytes) { asm volatile("cp.async.bulk.prefetch.L2.global [%0], %1;" ::"l"(p), "r"(bytes) : "memory"); }

__device__ __forceinline__ int fresh_tid() { int t; asm volatile("mov.u32 %0, %%tid.x;" : "=r"(t)); return t; }
__device__ __forceinline__ int fresh_bid() { int t; asm volatile("mov.u32 %0, %%ctaid.x;" : "=r"(t)); return t; }
#define IDS                                                                                                          \
  const int tid = fresh_tid(), wg = tid >> 7, wi = (tid >> 5) & 3, lane = tid & 31, g = lane >> 2, c = lane & 3;     \
  const int bid = fresh_bid(), tb = bid >> 3, hg = bid & 7, mh = wg & 1, kh = wg >> 1, t128 = tid & 127;             \
  const int lrow = mh * 64 + wi * 16 + g;                                                                            \
  (void)wi; (void)g; (void)c; (void)tb; (void)hg; (void)mh; (void)kh; (void)t128; (void)lrow; (void)lane;
__device__ __forceinline__ unsigned ticket_arrive(unsigned* ctr, unsigned n) {
  unsigned old;
  asm volatile("atom.add.release.gpu.global.u32 %0, [%1], 1;" : "=r"(old) : "l"(ctr) : "memory");
  return (old / n + 1) * n;
}
__device__ __forceinline__ void ticket_wait(unsigned* ctr, unsigned target) {
  for (int it = 0; it < (1 << 22); it++) {
    unsigned v;
    asm volatile("ld.acquire.gpu.global.u32 %0, [%1];" : "=r"(v) : "l"(ctr) : "memory");
    if ((int)(v - target) >= 0) break;
  }
}
__device__ __forceinline__ void mbar_wait(uint32_t bar, uint32_t parity) {
  for (int it = 0; it < (1 << 20); it++) {
    uint32_t ok;
    asm volatile("{\n.reg .pred p;\nmbarrier.try_wait.parity.shared::cta.b64 p, [%1], %2;\nselp.u32 %0, 1, 0, p;\n}\n" : "=r"(ok) : "r"(bar), "r"(parity) : "memory");
    if (__all_sync(0xffffffffu, ok)) break;
  }
}

struct PC { uint32_t msk, cb; };
__device__ __forceinline__ uint32_t exp2_sw(float u0, float u1, const PC& pc) {
  uint32_t w = __byte_perm(__float_as_uint(u0), __float_as_uint(u1), 0x6521);
  uint32_t g = lop3<0xEC>(w, 0x3F803F80u, pc.msk);
  uint32_t gp = lop3<0xCE>(w, 0xBF80BF80u, pc.msk);
  uint32_t t = hfma2(g, gp, 0x3FFF3FFFu);
  uint32_t q = hfma2(g, pc.cb, 0x3E4E3E4Eu);
  uint32_t m = hfma2(t, q, g);
  return lop3<0xD8>(w, m, pc.msk);
}
template <int HALF> __device__ __forceinline__ void softmax32(const float (&s)[16], uint32_t (&p)[8], const PC& pc) {
#pragma unroll
  for (int i = 0; i < 4; i++) {
    if ((PMASK >> (HALF * 4 + i)) & 1) {
      p[2 * i] = exp2_sw(s[4 * i], s[4 * i + 1], pc);
      p[2 * i + 1] = exp2_sw(s[4 * i + 2], s[4 * i + 3], pc);
    } else {
      p[2 * i] = pack_bf16(ex2(s[4 * i]), ex2(s[4 * i + 1]));
      p[2 * i + 1] = pack_bf16(ex2(s[4 * i + 2]), ex2(s[4 * i + 3]));
    }
  }
}
__device__ __forceinline__ uint32_t tile_off(int u) { return (uint32_t)((u >> 3) * 1536 + (u & 7) * 96); }
__device__ __forceinline__ void qk(float (&s)[16], const uint32_t (&q)[8], uint32_t kb) {
  wgmma_qk<24, 0>(s, q[0], q[1], q[2], q[3], kb + (8u << 16));
  wgmma_qk<24, 1>(s, q[4], q[5], q[6], q[7], kb + 16u);
}
__device__ __forceinline__ void pv(float (&o)[12], const uint32_t (&p)[8], uint32_t kb) {
  wgmma_pv<8, 1>(o, p[0], p[1], p[2], p[3], kb + 768u + (24u << 16));
  wgmma_pv<8, 1>(o, p[4], p[5], p[6], p[7], kb + 816u + (24u << 16));
}
template <int HALF> __device__ __forceinline__ void sm_pv(float (&s)[16], uint32_t (&p)[8], float (&o)[12], uint32_t kc, const PC& pc) {
  fence_regs(s); fence_regs(p);
  softmax32<HALF>(s, p, pc);
  fence_regs(p);
  wg_fence();
  pv(o, p, kc);
}
__device__ __forceinline__ void attn_fast(const uint32_t (&q)[8], float (&o)[12], uint32_t sb, const PC& pc) {
  const uint32_t kb = sb >> 4;
  float sA[16], sB[16];
  uint32_t pA[8], pB[8];
#pragma unroll
  for (int i = 0; i < 12; i++) o[i] = 0.f;
#pragma unroll
  for (int i = 0; i < 8; i++) { pA[i] = 0u; pB[i] = 0u; }
#pragma unroll
  for (int i = 0; i < 16; i++) { sA[i] = 0.f; sB[i] = 0.f; }
  mbar_wait(sb + SM_MBAR, 0);
  wg_fence();
  qk(sA, q, kb);
  wg_commit();
  wg_wait<0>();
#pragma unroll 1
  for (int c = 0; c < 8; c++) {
    const int c2 = (c + 1) & 7;
    mbar_wait(sb + SM_MBAR + c2 * 8, 0);
    const uint32_t kc = kb + c * 1536, kn = kb + c2 * 1536;
    wg_fence(); qk(sB, q, kc + 96); wg_commit();
    sm_pv<0>(sA, pA, o, kc, pc);           qk(sA, q, kc + 2 * 96); wg_commit(); wg_wait<1>();
    sm_pv<1>(sB, pB, o, kc + 96, pc);      qk(sB, q, kc + 3 * 96); wg_commit(); wg_wait<1>();
    sm_pv<0>(sA, pA, o, kc + 2 * 96, pc);  qk(sA, q, kc + 4 * 96); wg_commit(); wg_wait<1>();
    sm_pv<1>(sB, pB, o, kc + 3 * 96, pc);  qk(sB, q, kc + 5 * 96); wg_commit(); wg_wait<1>();
    sm_pv<0>(sA, pA, o, kc + 4 * 96, pc);  qk(sA, q, kc + 6 * 96); wg_commit(); wg_wait<1>();
    sm_pv<1>(sB, pB, o, kc + 5 * 96, pc);  qk(sB, q, kc + 7 * 96); wg_commit(); wg_wait<1>();
    sm_pv<0>(sA, pA, o, kc + 6 * 96, pc);  qk(sA, q, kn); wg_commit(); wg_wait<1>();
    sm_pv<1>(sB, pB, o, kc + 7 * 96, pc);  wg_commit(); wg_wait<1>();
    fence_regs(sA);
  }
  wg_wait<0>();
  fence_regs(o); fence_regs(pA); fence_regs(pB);
}

__device__ __forceinline__ void attn_safe(const uint32_t (&q)[8], float (&o)[12], uint32_t sb) {
  const uint32_t kb = sb >> 4;
  float s[16];
  uint32_t p[8];
  float m0 = -INFINITY, m1 = -INFINITY;
#pragma unroll
  for (int i = 0; i < 16; i++) s[i] = 0.f;
#pragma unroll
  for (int i = 0; i < 12; i++) o[i] = 0.f;
#pragma unroll 1
  for (int u = 0; u < 64; u++) {
    if ((u & 7) == 0) mbar_wait(sb + SM_MBAR + (u >> 3) * 8, 0);
    wg_fence();
    qk(s, q, kb + tile_off(u));
    wg_commit();
    wg_wait<0>();
    fence_regs(s);
#pragma unroll
    for (int b = 0; b < 4; b++) {
      const float sc = ((PMASK >> ((u & 1) * 4 + b)) & 1) ? 0.5f : 1.f;
      m0 = fmaxf(m0, sc * fmaxf(s[4 * b], s[4 * b + 1]));
      m1 = fmaxf(m1, sc * fmaxf(s[4 * b + 2], s[4 * b + 3]));
    }
  }
  m0 = fmaxf(m0, __shfl_xor_sync(~0u, m0, 1)); m0 = fmaxf(m0, __shfl_xor_sync(~0u, m0, 2));
  m1 = fmaxf(m1, __shfl_xor_sync(~0u, m1, 1)); m1 = fmaxf(m1, __shfl_xor_sync(~0u, m1, 2));
#pragma unroll 1
  for (int u = 0; u < 64; u++) {
    wg_fence();
    qk(s, q, kb + tile_off(u));
    wg_commit();
    wg_wait<0>();
    fence_regs(s);
#pragma unroll
    for (int b = 0; b < 4; b++) {
      const float sc = ((PMASK >> ((u & 1) * 4 + b)) & 1) ? 0.5f : 1.f;
      p[2 * b] = pack_bf16(ex2(fmaf(s[4 * b], sc, -m0)), ex2(fmaf(s[4 * b + 1], sc, -m0)));
      p[2 * b + 1] = pack_bf16(ex2(fmaf(s[4 * b + 2], sc, -m1)), ex2(fmaf(s[4 * b + 3], sc, -m1)));
    }
    fence_regs(p);
    wg_fence();
    pv(o, p, kb + tile_off(u));
    wg_commit();
    wg_wait<0>();
    fence_regs(o); fence_regs(p);
  }
}

__device__ __forceinline__ int b_slot(int k, int gstride) {
  const int kl = k >= 288 ? k - 288 : k;
  const int kg = kl < 160 ? (k >> 3) : (k >> 5) * 4 + (k & 2) + ((k >> 2) & 1);
  const int r = kl < 160 ? (k & 7) : ((k >> 3) & 3) * 2 + (k & 1);
  return kg * gstride + r * 16;
}
__device__ __forceinline__ void stage_w(uint32_t sb, const __nv_bfloat16* w, int hg, int tid) {
#pragma unroll
  for (int i = 0; i < 11; i++) {
    int idx = tid + 512 * i;
    if (idx < 5184) {
      int k = idx / 9, nb = idx - k * 9;
      cp_async16(sb + SM_W + b_slot(k, 1296) + nb * 144, w + k * DM + hg * 72 + nb * 8);
    }
  }
}
template <bool CG> __device__ __forceinline__ void load_a(uint32_t (&xa)[32], const __nv_bfloat16* a, uint32_t sa, int t128) {
  const __nv_bfloat16* p = a + (size_t)((t128 >> 5) * 16 + ((t128 & 31) >> 2)) * DM + 160 + (t128 & 3) * 8;
#pragma unroll
  for (int j = 0; j < 4; j++) {
    uint4 r0 = CG ? ldg_cg(p + j * 32) : ldg_nc(p + j * 32), r1 = CG ? ldg_cg(p + 8 * DM + j * 32) : ldg_nc(p + 8 * DM + j * 32);
    xa[8 * j] = r0.x; xa[8 * j + 1] = r1.x; xa[8 * j + 2] = r0.z; xa[8 * j + 3] = r1.z;
    xa[8 * j + 4] = r0.y; xa[8 * j + 5] = r1.y; xa[8 * j + 6] = r0.w; xa[8 * j + 7] = r1.w;
  }
#pragma unroll
  for (int i = 0; i < 10; i++) {
    const int row = (t128 >> 2) + (i & 1) * 32, ch = (i >> 1) * 4 + (t128 & 3);
    cp_async16(sa + (row >> 3) * 2880 + ch * 144 + (row & 7) * 16, a + (size_t)row * DM + ch * 8);
  }
}
template <int NR> __device__ __forceinline__ void gemm288(float (&acc)[NR], const uint32_t (&xa)[32], uint32_t sa, uint64_t wd, int wstep) {
  const uint64_t ad = make_desc(sa, 144, 2880);
#pragma unroll
  for (int j = 0; j < NR; j++) acc[j] = 0.f;
  wg_fence();
#pragma unroll
  for (int j = 0; j < 10; j++) wgmma_t(acc, ad + (uint64_t)(j * 18), wd + (uint64_t)(j * wstep), j > 0);
#pragma unroll
  for (int j = 0; j < 8; j++) wgmma_t(acc, xa[4 * j], xa[4 * j + 1], xa[4 * j + 2], xa[4 * j + 3], wd + (uint64_t)((10 + j) * wstep), 1);
  wg_commit();
  wg_wait<0>();
  fence_regs(acc);
}
__device__ __forceinline__ void ksplit_reduce(float (&res)[20], const float (&acc)[36], uint8_t* smem, int wg, int t128, int rs) {
  float* mine = (float*)(smem + wg * rs) + t128;
  const float* other = (const float*)(smem + (wg ^ 2) * rs) + t128;
  const bool hi = wg >= 2;
#pragma unroll
  for (int i = 0; i < 20; i++) mine[i * 128] = hi ? acc[i] : acc[i < 16 ? 20 + i : 0];
  bar_sync(1 + (wg & 1), 256);
#pragma unroll
  for (int i = 0; i < 20; i++) res[i] = (hi ? acc[i < 16 ? 20 + i : 0] : acc[i]) + other[i * 128];
}

__global__ void __launch_bounds__(512, 1)
fused_kernel(const __nv_bfloat16* __restrict__ x, const __nv_bfloat16* __restrict__ wq, const __nv_bfloat16* __restrict__ wk,
             const __nv_bfloat16* __restrict__ wv, const __nv_bfloat16* __restrict__ wo, const __nv_bfloat16* __restrict__ w_r,
             const __nv_bfloat16* __restrict__ w_gate, const __nv_bfloat16* __restrict__ w_up, const __nv_bfloat16* __restrict__ w_down,
             const __nv_bfloat16* __restrict__ gate_w, __nv_bfloat16* __restrict__ out, uint32_t zero) {
  extern __shared__ __align__(1024) uint8_t smem[];
  const uint32_t sb = (uint32_t)__cvta_generic_to_shared(smem);
  {
  IDS
  unsigned tgt_kv = 0;

  if (tid == 0) {
#pragma unroll
    for (int i = 0; i < 8; i++) asm volatile("mbarrier.init.shared::cta.b64 [%0], 1;" ::"r"(sb + SM_MBAR + i * 8) : "memory");
    if (hg >= 6) tgt_kv = ticket_arrive(&g_ctr[0], NCTA);
  }
  uint32_t xa[32];
  {
    uint4 ev[2];
    if (hg < 6) {
#pragma unroll
      for (int i = 0; i < 2; i++) {
        int k = tid + 512 * i;
        ev[i] = make_uint4(0, 0, 0, 0);
        if (k < DM) {
          const uint32_t* src = (const uint32_t*)((hg < 3 ? wk : wv) + k * 18) + (hg % 3) * 4;
          ev[i].x = __ldg(src);
          if (hg % 3 != 2) { ev[i].y = __ldg(src + 1); ev[i].z = __ldg(src + 2); ev[i].w = __ldg(src + 3); }
          else if (hg == 2) ev[i].y = (uint32_t)__bfloat16_as_ushort(w_r[k]) | ((uint32_t)__bfloat16_as_ushort(gate_w[k]) << 16);
        }
      }
    }
    load_a<false>(xa, x + (size_t)(tb * 128 + mh * 64) * DM + kh * 288, sb + wg * 23040, t128);
    asm volatile("cp.async.commit_group;" ::: "memory");
    stage_w(sb, wq, hg, tid);
    asm volatile("cp.async.commit_group;" ::: "memory");
    if (hg < 6) {
#pragma unroll
      for (int i = 0; i < 2; i++) {
        int k = tid + 512 * i;
        if (k < DM) *(uint4*)(smem + SM_EXT + b_slot(k, 128)) = ev[i];
      }
    }
  }
  asm volatile("cp.async.wait_group 1;" ::: "memory");
  fence_async();
  __syncthreads();
  if (hg < 6) {
    float e[4];
    gemm288(e, xa, sb + wg * 23040, make_desc(sb + SM_EXT + kh * 36 * 128, 128, 128), 16);
    float4* er = (float4*)(smem + SM_ERED) + mh * 128 + t128;
    if (kh == 1) *er = make_float4(e[0], e[1], e[2], e[3]);
    bar_sync(1 + mh, 256);
    if (kh == 0) {
      float4 o4 = *er;
      e[0] += o4.x; e[1] += o4.y; e[2] += o4.z; e[3] += o4.w;
      const int ch = hg % 3;
      float nrm = 0.f;
      unsigned long long best = 0ull;
#pragma unroll
      for (int h = 0; h < 2; h++) {
        const int key = tb * 128 + lrow + 8 * h;
        const bool poly = (PMASK >> ((key >> 3) & 7)) & 1;
        uint32_t v = pack_bf16(e[2 * h], e[2 * h + 1]);
        if (hg < 3) {
          float lo = bf_lo(v), hi = bf_hi(v);
          float n2 = (hg == 2 && c != 0) ? 0.f : lo * lo + hi * hi;
          n2 += __shfl_xor_sync(~0u, n2, 1);
          n2 += __shfl_xor_sync(~0u, n2, 2);
          nrm = fmaxf(nrm, n2);
          if (hg == 2 && c == 1) {
            g_gate[key] = rbf(sigmoidf_(hi));
            uint32_t rb = __float_as_uint(lo);
            rb = (rb & 0x80000000u) ? ~rb : (rb | 0x80000000u);
            unsigned long long cand = ((unsigned long long)rb << 32) | (uint32_t)(~key);
            best = cand > best ? cand : best;
          }
          if (poly) v = pack_bf16(2.f * lo, 2.f * hi);
          if (hg == 2 && c != 0) v = c == 1 ? (poly ? 0x44404000u : 0x00003F80u) : (c == 2 && poly ? 0x0000BFFFu : 0u);
        } else if (hg == 5 && c != 0) {
          v = c == 1 ? 0x00003F80u : 0u;
        }
        uint8_t* dst = (uint8_t*)g_kv + (key >> 8) * 24576 + (hg >= 3 ? 12288 : 0) + ((key >> 3) & 31) * 384 + ch * 128 + (key & 7) * 16 + c * 4;
        *(uint32_t*)dst = v;
      }
      if (hg < 3) {
#pragma unroll
        for (int o = 4; o < 32; o <<= 1) nrm = fmaxf(nrm, __shfl_xor_sync(~0u, nrm, o));
        if (lane == 0) ((float*)&g_kn[tb * 8 + mh * 4 + wi])[hg] = nrm;
        if (hg == 2) {
#pragma unroll
          for (int o = 1; o < 32; o <<= 1) { unsigned long long b2 = __shfl_xor_sync(~0u, best, o); best = b2 > best ? b2 : best; }
          if (lane == 0) g_best[tb * 8 + mh * 4 + wi] = best;
        }
      }
      fence_async_g();
      bar_sync(3, 256);
      if (tid == 0) tgt_kv = ticket_arrive(&g_ctr[0], NCTA);
    }
  }
  cp_async_wait_all();
  fence_async();
  __syncthreads();
  {
    float acc0[36], acc[20];
    gemm288(acc0, xa, sb + wg * 23040, make_desc(sb + SM_W + kh * 36 * 1296, 1296, 144), 162);
    ksplit_reduce(acc, acc0, smem, wg, t128, 23040);
    const float qs = 0.23570226039551584f * 1.4426950408889634f;
    uint8_t* qp = smem + SM_Q + lrow * 144 + kh * 80 + c * 4;
#pragma unroll
    for (int nb = 0; nb < 5; nb++) {
      if (nb < 4 || kh == 0) {
        *(uint32_t*)(qp + nb * 16) = pack_bf16(acc[4 * nb] * qs, acc[4 * nb + 1] * qs);
        *(uint32_t*)(qp + 8 * 144 + nb * 16) = pack_bf16(acc[4 * nb + 2] * qs, acc[4 * nb + 3] * qs);
      }
    }
  }
  fence_async();
  __syncthreads();
  if (tid == 0) {
    ticket_wait(&g_ctr[0], tgt_kv);
    fence_async_g();
#pragma unroll
    for (int i = 0; i < 8; i++) {
      asm volatile("mbarrier.arrive.expect_tx.shared::cta.b64 _, [%0], 24576;" ::"r"(sb + SM_MBAR + i * 8) : "memory");
      asm volatile("cp.async.bulk.shared::cluster.global.mbarrier::complete_tx::bytes [%0], [%1], 24576, [%2];"
                   ::"r"(sb + i * 24576), "l"((const uint8_t*)g_kv + i * 24576), "r"(sb + SM_MBAR + i * 8) : "memory");
    }
    prefetch_l2((const uint8_t*)wo + bid * 5184, 5184);
    prefetch_l2((const uint8_t*)w_gate + bid * 41472, 41472);
    prefetch_l2((const uint8_t*)w_up + bid * 41472, 41472);
    prefetch_l2((const uint8_t*)w_down + bid * 41472, 41472);
  }
  __syncthreads();
  {
    float kmax = 0.f;
#pragma unroll
    for (int i = 0; i < 4; i++) { float4 v = g_kn[lane + 32 * i]; kmax = fmaxf(kmax, v.x + v.y + v.z); }
#pragma unroll
    for (int o = 1; o < 32; o <<= 1) kmax = fmaxf(kmax, __shfl_xor_sync(~0u, kmax, o));
    if (lane == 0) *(volatile float*)(smem + SM_MISC + 512 + (tid >> 5) * 4) = kmax;
    __syncwarp();
  }
  }
  {
    PC pc; pc.msk = 0x007F007Fu + zero; pc.cb = 0x3DCD3DCDu + zero;
#pragma unroll 1
    for (int pass = 0; pass < 2; pass++) {
      uint32_t q[8];
      uint32_t unsafe;
      {
      IDS
      const float kmax = *(volatile float*)(smem + SM_MISC + 512 + (tid >> 5) * 4);
      const int r0 = pass * 64 + wi * 16 + g;
      const uint8_t* qp = smem + SM_Q + r0 * 144 + wg * 36 + c * 4;
      q[0] = *(const uint32_t*)qp; q[1] = *(const uint32_t*)(qp + 8 * 144);
      q[2] = *(const uint32_t*)(qp + 16); q[3] = *(const uint32_t*)(qp + 8 * 144 + 16);
      q[4] = c == 0 ? *(const uint32_t*)(qp + 32) : 0u; q[5] = c == 0 ? *(const uint32_t*)(qp + 8 * 144 + 32) : 0u;
      float n0 = bf_lo(q[0]) * bf_lo(q[0]) + bf_hi(q[0]) * bf_hi(q[0]) + bf_lo(q[2]) * bf_lo(q[2]) + bf_hi(q[2]) * bf_hi(q[2]) + bf_lo(q[4]) * bf_lo(q[4]) + bf_hi(q[4]) * bf_hi(q[4]);
      float n1 = bf_lo(q[1]) * bf_lo(q[1]) + bf_hi(q[1]) * bf_hi(q[1]) + bf_lo(q[3]) * bf_lo(q[3]) + bf_hi(q[3]) * bf_hi(q[3]) + bf_lo(q[5]) * bf_lo(q[5]) + bf_hi(q[5]) * bf_hi(q[5]);
      n0 += __shfl_xor_sync(~0u, n0, 1); n0 += __shfl_xor_sync(~0u, n0, 2);
      n1 += __shfl_xor_sync(~0u, n1, 1); n1 += __shfl_xor_sync(~0u, n1, 2);
      const float m0 = ceilf(sqrtf(n0 * kmax) * 1.001f + 0.01f), m1 = ceilf(sqrtf(n1 * kmax) * 1.001f + 0.01f);
      asm volatile("{\n.reg .pred p, r;\nsetp.ne.u32 p, %1, 0;\nbarrier.cta.red.or.pred.aligned r, %2, 128, p;\nselp.u32 %0, 1, 0, r;\n}\n"
                   : "=r"(unsafe) : "r"((uint32_t)!(m0 <= 60.f && m1 <= 60.f)), "r"(4 + wg) : "memory");
      q[6] = unsafe ? 0u : c == 1 ? pack_bf16(-m0, 1.f) : c == 2 ? 0x3F803F80u : 0u;
      q[7] = unsafe ? 0u : c == 1 ? pack_bf16(-m1, 1.f) : c == 2 ? 0x3F803F80u : 0u;
      }
      float o[12];
      if (!__any_sync(0xffffffffu, unsafe)) {
        attn_fast(q, o, sb, pc);
      } else {
        attn_safe(q, o, sb);
      }
      IDS
      const float i0 = 1.f / __shfl_sync(~0u, o[8], (lane & ~3) | 1), i1 = 1.f / __shfl_sync(~0u, o[10], (lane & ~3) | 1);
      uint8_t* ob = (uint8_t*)g_o + tb * 147456 + (pass + 2 * (hg >> 2)) * 36864 + wi * 9216 + g * 16;
      const int c0 = (hg & 3) * 72 + wg * 18 + 2 * c;
      uint8_t* p0 = ob + (c0 >> 3) * 128 + (c0 & 7) * 2;
      *(uint32_t*)p0 = pack_bf16(o[0] * i0, o[1] * i0); *(uint32_t*)(p0 + 4608) = pack_bf16(o[2] * i1, o[3] * i1);
      *(uint32_t*)(p0 + 128) = pack_bf16(o[4] * i0, o[5] * i0); *(uint32_t*)(p0 + 4608 + 128) = pack_bf16(o[6] * i1, o[7] * i1);
      if (c == 0) { *(uint32_t*)(p0 + 256) = pack_bf16(o[8] * i0, o[9] * i0); *(uint32_t*)(p0 + 4608 + 256) = pack_bf16(o[10] * i1, o[11] * i1); }
    }
  }
  fence_async_g();
  __syncthreads();
  IDS
  unsigned tgt_o = 0, tgt_y = 0;
  if (tid == 0) tgt_o = ticket_arrive(&g_ctr[32 * (1 + tb)], 8);
#pragma unroll
  for (int i = 0; i < 11; i++) {
    const int idx = tid + 512 * i;
    if (idx < 5184) {
      const int kg = idx / 72, rem = idx - kg * 72;
      cp_async16(sb + SM_W3 + idx * 16, wo + (kg * 8 + (rem & 7)) * DM + hg * 72 + (rem >> 3) * 8);
    }
  }

  int sel;
  float rsel;
  {
    uint2 wgv[12], wuv[12];
    uint4 wdv[6];
    const int q9 = tid % 9, rg = tid / 9, c72 = tid % 72, r6 = tid / 72;
    if (tid < 432) {
#pragma unroll
      for (int i = 0; i < 12; i++) {
        size_t off = (size_t)(rg + 48 * i) * FF + bid * 36 + q9 * 4;
        wgv[i] = ldg_nc2(w_gate + off); wuv[i] = ldg_nc2(w_up + off);
      }
#pragma unroll
      for (int i = 0; i < 6; i++) wdv[i] = ldg_nc(w_down + (size_t)(bid * 36 + r6 * 6 + i) * DM + c72 * 8);
    }
    unsigned long long best = 0ull;
#pragma unroll
    for (int i = 0; i < 4; i++) { unsigned long long b2 = g_best[lane + 32 * i]; best = b2 > best ? b2 : best; }
#pragma unroll
    for (int o = 1; o < 32; o <<= 1) { unsigned long long b2 = __shfl_xor_sync(~0u, best, o); best = b2 > best ? b2 : best; }
    sel = (int)(~(uint32_t)best) & (S_LEN - 1);
    uint32_t rb = (uint32_t)(best >> 32);
    rb = (rb & 0x80000000u) ? (rb & 0x7FFFFFFFu) : ~rb;
    rsel = rbf(sigmoidf_(__uint_as_float(rb)));
    float* m1 = (float*)(smem + SM_MOE1);
    float* m2 = (float*)(smem + SM_MOE2);
    float* hs = (float*)(smem + SM_MISC);
    if (tid < 432) {
      float ga[4] = {0.f, 0.f, 0.f, 0.f}, ua[4] = {0.f, 0.f, 0.f, 0.f};
#pragma unroll
      for (int i = 0; i < 12; i++) {
        float xv = __bfloat162float(x[(size_t)sel * DM + rg + 48 * i]);
        ga[0] = fmaf(xv, bf_lo(wgv[i].x), ga[0]); ga[1] = fmaf(xv, bf_hi(wgv[i].x), ga[1]);
        ga[2] = fmaf(xv, bf_lo(wgv[i].y), ga[2]); ga[3] = fmaf(xv, bf_hi(wgv[i].y), ga[3]);
        ua[0] = fmaf(xv, bf_lo(wuv[i].x), ua[0]); ua[1] = fmaf(xv, bf_hi(wuv[i].x), ua[1]);
        ua[2] = fmaf(xv, bf_lo(wuv[i].y), ua[2]); ua[3] = fmaf(xv, bf_hi(wuv[i].y), ua[3]);
      }
      *(float4*)(m1 + rg * 72 + q9 * 4) = make_float4(ga[0], ga[1], ga[2], ga[3]);
      *(float4*)(m1 + rg * 72 + 36 + q9 * 4) = make_float4(ua[0], ua[1], ua[2], ua[3]);
    }
    __syncthreads();
    if (tid < 432) {
      float s = 0.f;
#pragma unroll
      for (int i = 0; i < 8; i++) s += m1[(r6 * 8 + i) * 72 + c72];
      m2[r6 * 72 + c72] = s;
    }
    __syncthreads();
    if (tid < 36) {
      float gs = 0.f, us = 0.f;
#pragma unroll
      for (int i = 0; i < 6; i++) { gs += m2[i * 72 + tid]; us += m2[i * 72 + 36 + tid]; }
      gs = rbf(gs); us = rbf(us);
      hs[tid] = rbf(rbf(gs * sigmoidf_(gs)) * us);
    }
    __syncthreads();
    if (tid < 432) {
      float y[8] = {0.f, 0.f, 0.f, 0.f, 0.f, 0.f, 0.f, 0.f};
#pragma unroll
      for (int i = 0; i < 6; i++) {
        float hv = hs[r6 * 6 + i];
        y[0] = fmaf(hv, bf_lo(wdv[i].x), y[0]); y[1] = fmaf(hv, bf_hi(wdv[i].x), y[1]);
        y[2] = fmaf(hv, bf_lo(wdv[i].y), y[2]); y[3] = fmaf(hv, bf_hi(wdv[i].y), y[3]);
        y[4] = fmaf(hv, bf_lo(wdv[i].z), y[4]); y[5] = fmaf(hv, bf_hi(wdv[i].z), y[5]);
        y[6] = fmaf(hv, bf_lo(wdv[i].w), y[6]); y[7] = fmaf(hv, bf_hi(wdv[i].w), y[7]);
      }
      *(float4*)(m1 + r6 * DM + c72 * 8) = make_float4(y[0], y[1], y[2], y[3]);
      *(float4*)(m1 + r6 * DM + c72 * 8 + 4) = make_float4(y[4], y[5], y[6], y[7]);
    }
    __syncthreads();
    if (tid < 288) {
      float2 s = make_float2(0.f, 0.f);
#pragma unroll
      for (int i = 0; i < 6; i++) { float2 v = *(float2*)(m1 + i * DM + tid * 2); s.x += v.x; s.y += v.y; }
      *(float2*)(g_ypart + bid * DM + tid * 2) = s;
    }
    cp_async_wait_all();
    fence_async();
    __syncthreads();
    if (tid == 0) {
      tgt_y = ticket_arrive(&g_ctr[32 * 17], NCTA);
      ticket_wait(&g_ctr[32 * (1 + tb)], tgt_o);
      fence_async_g();
#pragma unroll
      for (int i = 0; i < 4; i++) {
        asm volatile("mbarrier.arrive.expect_tx.shared::cta.b64 _, [%0], 36864;" ::"r"(sb + SM_MBAR + i * 8) : "memory");
        asm volatile("cp.async.bulk.shared::cluster.global.mbarrier::complete_tx::bytes [%0], [%1], 36864, [%2];"
                     ::"r"(sb + i * 36864), "l"((const uint8_t*)g_o + tb * 147456 + i * 36864), "r"(sb + SM_MBAR + i * 8) : "memory");
      }
    }
  }

  {
    const int row = tb * 128 + lrow;
    const int nb0 = kh == 0 ? 0 : 5;
    uint32_t xr[10];
    {
      const uint32_t* xp = (const uint32_t*)(x + (size_t)row * DM + hg * 72 + nb0 * 8) + c;
#pragma unroll
      for (int i = 0; i < 5; i++) {
        xr[2 * i] = (i < 4 || kh == 0) ? __ldg(xp + i * 4) : 0u;
        xr[2 * i + 1] = (i < 4 || kh == 0) ? __ldg(xp + 4 * DM + i * 4) : 0u;
      }
    }
    const float g0 = g_gate[row], g1 = g_gate[row + 8];
    float acc0[36], acc[20];
    {
      const uint64_t ad = make_desc(sb + wg * 36864, 128, 4608), wd = make_desc(sb + SM_W3 + kh * 36 * 1152, 1152, 128);
#pragma unroll
      for (int j = 0; j < 36; j++) acc0[j] = 0.f;
      mbar_wait(sb + SM_MBAR + wg * 8, 1);
      wg_fence();
#pragma unroll
      for (int j = 0; j < 18; j++) wgmma_t(acc0, ad + (uint64_t)(j * 16), wd + (uint64_t)(j * 144), 1);
      wg_commit();
      wg_wait<0>();
      fence_regs(acc0);
    }
    ksplit_reduce(acc, acc0, smem, wg, t128, 36864);
    float* upd = (float*)(smem + SM_MISC);
    const bool owner = (sel >> 7) == tb;
    if (owner) {
      float* m2 = (float*)(smem + SM_W3);
      if (tid == 0) ticket_wait(&g_ctr[32 * 17], tgt_y);
      __syncthreads();
      if (tid < 288) {
        const int c72 = tid % 72, pt = tid / 72;
        float s = 0.f;
#pragma unroll 8
        for (int i = 0; i < 32; i++) s += __ldcg(g_ypart + (pt * 32 + i) * DM + hg * 72 + c72);
        m2[tid] = s;
      }
      __syncthreads();
      if (tid < 72) upd[tid] = rbf(rbf(m2[tid] + m2[72 + tid] + m2[144 + tid] + m2[216 + tid]) * rsel);
      __syncthreads();
    }
    const float h0 = rbf(1.f - g0), h1 = rbf(1.f - g1);
    uint32_t* op = (uint32_t*)(out + (size_t)row * DM + hg * 72 + nb0 * 8) + c;
#pragma unroll
    for (int i = 0; i < 5; i++) {
      if (i < 4 || kh == 0) {
        const float a0 = acc[4 * i], a1 = acc[4 * i + 1], a2 = acc[4 * i + 2], a3 = acc[4 * i + 3];
        const uint32_t x0 = xr[2 * i], x1 = xr[2 * i + 1];
        float b0 = bf_lo(x0), b1 = bf_hi(x0), b2 = bf_lo(x1), b3 = bf_hi(x1);
        if (owner) {
          const int col = (nb0 + i) * 8 + c * 2;
          if (row == sel) { b0 = rbf(b0 + upd[col]); b1 = rbf(b1 + upd[col + 1]); }
          if (row + 8 == sel) { b2 = rbf(b2 + upd[col]); b3 = rbf(b3 + upd[col + 1]); }
        }
        op[i * 4] = pack_bf16(rbf(g0 * rbf(a0)) + rbf(h0 * b0), rbf(g0 * rbf(a1)) + rbf(h0 * b1));
        op[4 * DM + i * 4] = pack_bf16(rbf(g1 * rbf(a2)) + rbf(h1 * b2), rbf(g1 * rbf(a3)) + rbf(h1 * b3));
      }
    }
  }
}

extern "C" void kernel_launch(void* const* d_in, const int* in_sizes, int n_in, void* d_out, int out_size) {
  cudaFuncSetAttribute(fused_kernel, cudaFuncAttributeMaxDynamicSharedMemorySize, SM_TOTAL);
  typedef const __nv_bfloat16* P;
  fused_kernel<<<NCTA, 512, SM_TOTAL, cudaStreamPerThread>>>((P)d_in[0], (P)d_in[1], (P)d_in[2], (P)d_in[3], (P)d_in[4], (P)d_in[6],
                                                            (P)d_in[7], (P)d_in[8], (P)d_in[9], (P)d_in[10], (__nv_bfloat16*)d_out, 0u);
}
```

```cpp
#include <cuda_runtime.h>
#include <cuda.h>
#include <cuda_bf16.h>
#include <stdint.h>

#define S_LEN 2048
#define DM 576
#define FF 4608
#define NCTA 128
#define PMASK 0xB5u

__device__ uint4 g_kv[8 * 1536];
__device__ float4 g_kn[128];
__device__ unsigned long long g_best[128];
__device__ float g_gate[S_LEN];
__device__ uint4 g_o[S_LEN * DM / 8];
__device__ float g_ypart[NCTA * DM];
__device__ unsigned g_ctr[32 * 32];

#define TS(k)
#define TS2(k)
#define WNB 9232
#define SM_W1 147456
#define SM_Q 196608
#define SM_SV 215040
#define SM_W3 0
#define SM_O 83200
#define SM_MBAR 230656
#define MB_X 0
#define MB_KV 72
#define MB_O 136
#define MB_W1 168
#define MB_W3 176
#define SM_MISC 230912
#define SM_TOTAL 231424
#define NTHR 640

__device__ __forceinline__ uint64_t make_desc(uint32_t saddr, uint32_t lbo, uint32_t sbo) {
  return (uint64_t)((saddr & 0x3FFFF) >> 4) | ((uint64_t)(lbo >> 4) << 16) | ((uint64_t)(sbo >> 4) << 32);
}
__device__ __forceinline__ void wg_fence() { asm volatile("wgmma.fence.sync.aligned;" ::: "memory"); }
__device__ __forceinline__ void wg_commit() { asm volatile("wgmma.commit_group.sync.aligned;" ::: "memory"); }
template <int N> __device__ __forceinline__ void wg_wait() { asm volatile("wgmma.wait_group.sync.aligned %0;" ::"n"(N) : "memory"); }
__device__ __forceinline__ void wgmma_t(float (&d)[4], uint64_t da, uint64_t db, int sd) {
  asm volatile("{\n.reg .pred p;\nsetp.ne.b32 p, %6, 0;\n"
    "wgmma.mma_async.sync.aligned.m64n8k16.f32.bf16.bf16 "
    "{%0,%1,%2,%3}, %4, %5, p, 1, 1, 0, 1;\n}\n"
    : "+f"(d[0]),"+f"(d[1]),"+f"(d[2]),"+f"(d[3])
    : "l"(da),"l"(db),"r"(sd));
}
__device__ __forceinline__ void wgmma_t(float (&d)[36], uint64_t da, uint64_t db, int sd) {
  asm volatile("{\n.reg .pred p;\nsetp.ne.b32 p, %38, 0;\n"
    "wgmma.mma_async.sync.aligned.m64n72k16.f32.bf16.bf16 "
    "{%0,%1,%2,%3,%4,%5,%6,%7,%8,%9,%10,%11,%12,%13,%14,%15,%16,%17,%18,%19,%20,%21,%22,%23,%24,%25,%26,%27,%28,%29,%30,%31,%32,%33,%34,%35}, %36, %37, p, 1, 1, 0, 1;\n}\n"
    : "+f"(d[0]),"+f"(d[1]),"+f"(d[2]),"+f"(d[3]),"+f"(d[4]),"+f"(d[5]),"+f"(d[6]),"+f"(d[7]),"+f"(d[8]),"+f"(d[9]),"+f"(d[10]),"+f"(d[11]),"+f"(d[12]),"+f"(d[13]),"+f"(d[14]),"+f"(d[15]),"+f"(d[16]),"+f"(d[17]),"+f"(d[18]),"+f"(d[19]),"+f"(d[20]),"+f"(d[21]),"+f"(d[22]),"+f"(d[23]),"+f"(d[24]),"+f"(d[25]),"+f"(d[26]),"+f"(d[27]),"+f"(d[28]),"+f"(d[29]),"+f"(d[30]),"+f"(d[31]),"+f"(d[32]),"+f"(d[33]),"+f"(d[34]),"+f"(d[35])
    : "l"(da),"l"(db),"r"(sd));
}
template <int HI, int SD> __device__ __forceinline__ void wgmma_pv(float (&d)[12], uint32_t a0, uint32_t a1, uint32_t a2, uint32_t a3, uint32_t lo) {
  asm volatile("{\n.reg .pred p;\n.reg .b64 db;\nsetp.ne.b32 p, %18, 0;\nmov.b64 db, {%16, %17};\n"
    "wgmma.mma_async.sync.aligned.m64n24k16.f32.bf16.bf16 "
    "{%0,%1,%2,%3,%4,%5,%6,%7,%8,%9,%10,%11}, {%12,%13,%14,%15}, db, p, 1, 1, 1;\n}\n"
    : "+f"(d[0]),"+f"(d[1]),"+f"(d[2]),"+f"(d[3]),"+f"(d[4]),"+f"(d[5]),"+f"(d[6]),"+f"(d[7]),"+f"(d[8]),"+f"(d[9]),"+f"(d[10]),"+f"(d[11])
    : "r"(a0),"r"(a1),"r"(a2),"r"(a3),"r"(lo),"n"(HI),"n"(SD));
}
template <int HI, int SD> __device__ __forceinline__ void wgmma_qk(float (&d)[16], uint32_t a0, uint32_t a1, uint32_t a2, uint32_t a3, uint32_t lo) {
  asm volatile("{\n.reg .pred p;\n.reg .b64 db;\nsetp.ne.b32 p, %22, 0;\nmov.b64 db, {%20, %21};\n"
    "wgmma.mma_async.sync.aligned.m64n32k16.f32.bf16.bf16 "
    "{%0,%1,%2,%3,%4,%5,%6,%7,%8,%9,%10,%11,%12,%13,%14,%15}, {%16,%17,%18,%19}, db, p, 1, 1, 0;\n}\n"
    : "+f"(d[0]),"+f"(d[1]),"+f"(d[2]),"+f"(d[3]),"+f"(d[4]),"+f"(d[5]),"+f"(d[6]),"+f"(d[7]),"+f"(d[8]),"+f"(d[9]),"+f"(d[10]),"+f"(d[11]),"+f"(d[12]),"+f"(d[13]),"+f"(d[14]),"+f"(d[15])
    : "r"(a0),"r"(a1),"r"(a2),"r"(a3),"r"(lo),"n"(HI),"n"(SD));
}

template <int N> __device__ __forceinline__ void fence_regs(float (&s)[N]) {
#pragma unroll
  for (int i = 0; i < N; i++) asm volatile("" : "+f"(s[i])::"memory");
}
template <int N> __device__ __forceinline__ void fence_regs(uint32_t (&s)[N]) {
#pragma unroll
  for (int i = 0; i < N; i++) asm volatile("" : "+r"(s[i])::"memory");
}
__device__ __forceinline__ float ex2(float x) { float r; asm("ex2.approx.ftz.f32 %0, %1;" : "=f"(r) : "f"(x)); return r; }
__device__ __forceinline__ uint32_t pack_bf16(float lo, float hi) { uint32_t r; asm("cvt.rn.bf16x2.f32 %0, %1, %2;" : "=r"(r) : "f"(hi), "f"(lo)); return r; }
__device__ __forceinline__ float bf_lo(uint32_t v) { return __uint_as_float(v << 16); }
__device__ __forceinline__ float bf_hi(uint32_t v) { return __uint_as_float(v & 0xFFFF0000u); }
__device__ __forceinline__ float rbf(float x) { return __uint_as_float(pack_bf16(0.f, x)); }
__device__ __forceinline__ uint32_t hfma2(uint32_t a, uint32_t b, uint32_t c) { uint32_t r; asm("fma.rn.bf16x2 %0, %1, %2, %3;" : "=r"(r) : "r"(a), "r"(b), "r"(c)); return r; }
template <int LUT> __device__ __forceinline__ uint32_t lop3(uint32_t a, uint32_t b, uint32_t c) { uint32_t r; asm("lop3.b32 %0, %1, %2, %3, %4;" : "=r"(r) : "r"(a), "r"(b), "r"(c), "n"(LUT)); return r; }
__device__ __forceinline__ float sigmoidf_(float x) { return 1.f / (1.f + __expf(-x)); }
__device__ __forceinline__ void bar_sync(int id, int n) { asm volatile("bar.sync %0, %1;" ::"r"(id), "r"(n) : "memory"); }
__device__ __forceinline__ void bar_arrive(int id, int n) { asm volatile("bar.arrive %0, %1;" ::"r"(id), "r"(n) : "memory"); }
__device__ __forceinline__ void mbar_arrive(uint32_t bar) { asm volatile("mbarrier.arrive.shared::cta.b64 _, [%0];" ::"r"(bar) : "memory"); }
__device__ __forceinline__ void bulk_load(uint32_t dst, const void* src, uint32_t bytes, uint32_t bar) {
  asm volatile("mbarrier.arrive.expect_tx.shared::cta.b64 _, [%0], %1;" ::"r"(bar), "r"(bytes) : "memory");
  asm volatile("cp.async.bulk.shared::cluster.global.mbarrier::complete_tx::bytes [%0], [%1], %2, [%3];" ::"r"(dst), "l"(src), "r"(bytes), "r"(bar) : "memory");
}
__device__ __forceinline__ void fence_async() { asm volatile("fence.proxy.async.shared::cta;" ::: "memory"); }
__device__ __forceinline__ void fence_async_g() { asm volatile("fence.proxy.async.global;" ::: "memory"); }
__device__ __forceinline__ void cp_async16(uint32_t dst, const void* src) { asm volatile("cp.async.cg.shared.global [%0], [%1], 16;" ::"r"(dst), "l"(src) : "memory"); }
__device__ __forceinline__ void cp_async_wait_all() { asm volatile("cp.async.wait_all;" ::: "memory"); }
__device__ __forceinline__ uint4 ldg_nc(const void* p) { uint4 v; asm volatile("ld.global.nc.L1::no_allocate.v4.u32 {%0,%1,%2,%3}, [%4];" : "=r"(v.x), "=r"(v.y), "=r"(v.z), "=r"(v.w) : "l"(p)); return v; }
__device__ __forceinline__ uint2 ldg_nc2(const void* p) { uint2 v; asm volatile("ld.global.nc.L1::no_allocate.v2.u32 {%0,%1}, [%2];" : "=r"(v.x), "=r"(v.y) : "l"(p)); return v; }
__device__ __forceinline__ uint4 ldg_cg(const void* p) { uint4 v; asm volatile("ld.global.cg.v4.u32 {%0,%1,%2,%3}, [%4];" : "=r"(v.x), "=r"(v.y), "=r"(v.z), "=r"(v.w) : "l"(p) : "memory"); return v; }
__device__ __forceinline__ void prefetch_l2(const void* p, uint32_t bytes) { asm volatile("cp.async.bulk.prefetch.L2.global [%0], %1;" ::"l"(p), "r"(bytes) : "memory"); }

__device__ __forceinline__ int fresh_tid() { int t; asm volatile("mov.u32 %0, %%tid.x;" : "=r"(t)); return t; }
__device__ __forceinline__ int fresh_bid() { int t; asm volatile("mov.u32 %0, %%ctaid.x;" : "=r"(t)); return t; }
#define IDS                                                                                                          \
  const int tid = fresh_tid(), wg = tid >> 7, wi = (tid >> 5) & 3, lane = tid & 31, g = lane >> 2, c = lane & 3;     \
  const int bid = fresh_bid(), tb = bid >> 3, hg = bid & 7, mh = wg & 1, kh = wg >> 1, t128 = tid & 127;             \
  const int lrow = mh * 64 + wi * 16 + g;                                                                            \
  (void)wi; (void)g; (void)c; (void)tb; (void)hg; (void)mh; (void)kh; (void)t128; (void)lrow; (void)lane;
__device__ __forceinline__ unsigned ticket_arrive(unsigned* ctr, unsigned n) {
  unsigned old;
  asm volatile("atom.add.release.gpu.global.u32 %0, [%1], 1;" : "=r"(old) : "l"(ctr) : "memory");
  return (old / n + 1) * n;
}
__device__ __forceinline__ void ticket_wait(unsigned* ctr, unsigned target) {
  for (int it = 0; it < (1 << 22); it++) {
    unsigned v;
    asm volatile("ld.acquire.gpu.global.u32 %0, [%1];" : "=r"(v) : "l"(ctr) : "memory");
    if ((int)(v - target) >= 0) break;
  }
}
__device__ __forceinline__ void mbar_wait(uint32_t bar, uint32_t parity) {
  for (int it = 0; it < (1 << 20); it++) {
    uint32_t ok;
    asm volatile("{\n.reg .pred p;\nmbarrier.try_wait.parity.shared::cta.b64 p, [%1], %2;\nselp.u32 %0, 1, 0, p;\n}\n" : "=r"(ok) : "r"(bar), "r"(parity) : "memory");
    if (__all_sync(0xffffffffu, ok)) break;
  }
}

struct PC { uint32_t msk, cb; };
__device__ __forceinline__ uint32_t exp2_sw(float u0, float u1, const PC& pc) {
  uint32_t w = __byte_perm(__float_as_uint(u0), __float_as_uint(u1), 0x6521);
  uint32_t g = lop3<0xEC>(w, 0x3F803F80u, pc.msk);
  uint32_t gp = lop3<0xCE>(w, 0xBF80BF80u, pc.msk);
  uint32_t t = hfma2(g, gp, 0x3FFF3FFFu);
  uint32_t q = hfma2(g, pc.cb, 0x3E4E3E4Eu);
  uint32_t m = hfma2(t, q, g);
  return lop3<0xD8>(w, m, pc.msk);
}
template <int HALF> __device__ __forceinline__ void softmax32(const float (&s)[16], uint32_t (&p)[8], const PC& pc) {
#pragma unroll
  for (int i = 0; i < 4; i++) {
    if ((PMASK >> (HALF * 4 + i)) & 1) {
      p[2 * i] = exp2_sw(s[4 * i], s[4 * i + 1], pc);
      p[2 * i + 1] = exp2_sw(s[4 * i + 2], s[4 * i + 3], pc);
    } else {
      p[2 * i] = pack_bf16(ex2(s[4 * i]), ex2(s[4 * i + 1]));
      p[2 * i + 1] = pack_bf16(ex2(s[4 * i + 2]), ex2(s[4 * i + 3]));
    }
  }
}
__device__ __forceinline__ uint32_t tile_off(int u) { return (uint32_t)((u >> 3) * 1536 + (u & 7) * 96); }
__device__ __forceinline__ void qk(float (&s)[16], const uint32_t (&q)[8], uint32_t kb) {
  wgmma_qk<24, 0>(s, q[0], q[1], q[2], q[3], kb + (8u << 16));
  wgmma_qk<24, 1>(s, q[4], q[5], q[6], q[7], kb + 16u);
}
__device__ __forceinline__ void pv(float (&o)[12], const uint32_t (&p)[8], uint32_t kb) {
  wgmma_pv<8, 1>(o, p[0], p[1], p[2], p[3], kb + 768u + (24u << 16));
  wgmma_pv<8, 1>(o, p[4], p[5], p[6], p[7], kb + 816u + (24u << 16));
}
template <int HALF> __device__ __forceinline__ void sm_pv(float (&s)[16], uint32_t (&p)[8], float (&o)[12], uint32_t kc, const PC& pc) {
  fence_regs(s); fence_regs(p);
  softmax32<HALF>(s, p, pc);
  fence_regs(p);
  wg_fence();
  pv(o, p, kc);
}
__device__ __forceinline__ void attn_fast(const uint32_t (&q)[8], float (&o)[12], uint32_t sb, const PC& pc, int sig) {
  const uint32_t kb = sb >> 4;
  float sA[16], sB[16];
  uint32_t pA[8], pB[8];
#pragma unroll
  for (int i = 0; i < 12; i++) o[i] = 0.f;
#pragma unroll
  for (int i = 0; i < 8; i++) { pA[i] = 0u; pB[i] = 0u; }
#pragma unroll
  for (int i = 0; i < 16; i++) { sA[i] = 0.f; sB[i] = 0.f; }
  mbar_wait(sb + SM_MBAR + MB_KV, 0);
  wg_fence();
  qk(sA, q, kb);
  wg_commit();
  wg_wait<0>();
#pragma unroll 1
  for (int c = 0; c < 8; c++) {
    const int c2 = (c + 1) & 7;
    mbar_wait(sb + SM_MBAR + MB_KV + c2 * 8, 0);
    if (c == sig) bar_arrive(10, NTHR);
    const uint32_t kc = kb + c * 1536, kn = kb + c2 * 1536;
    wg_fence(); qk(sB, q, kc + 96); wg_commit();
    sm_pv<0>(sA, pA, o, kc, pc);           qk(sA, q, kc + 2 * 96); wg_commit(); wg_wait<1>();
    sm_pv<1>(sB, pB, o, kc + 96, pc);      qk(sB, q, kc + 3 * 96); wg_commit(); wg_wait<1>();
    sm_pv<0>(sA, pA, o, kc + 2 * 96, pc);  qk(sA, q, kc + 4 * 96); wg_commit(); wg_wait<1>();
    sm_pv<1>(sB, pB, o, kc + 3 * 96, pc);  qk(sB, q, kc + 5 * 96); wg_commit(); wg_wait<1>();
    sm_pv<0>(sA, pA, o, kc + 4 * 96, pc);  qk(sA, q, kc + 6 * 96); wg_commit(); wg_wait<1>();
    sm_pv<1>(sB, pB, o, kc + 5 * 96, pc);  qk(sB, q, kc + 7 * 96); wg_commit(); wg_wait<1>();
    sm_pv<0>(sA, pA, o, kc + 6 * 96, pc);  qk(sA, q, kn); wg_commit(); wg_wait<1>();
    sm_pv<1>(sB, pB, o, kc + 7 * 96, pc);  wg_commit(); wg_wait<1>();
    fence_regs(sA);
  }
  wg_wait<0>();
  fence_regs(o); fence_regs(pA); fence_regs(pB);
}

__device__ __forceinline__ void attn_safe(const uint32_t (&q)[8], float (&o)[12], uint32_t sb) {
  const uint32_t kb = sb >> 4;
  float s[16];
  uint32_t p[8];
  float m0 = -INFINITY, m1 = -INFINITY;
#pragma unroll
  for (int i = 0; i < 16; i++) s[i] = 0.f;
#pragma unroll
  for (int i = 0; i < 12; i++) o[i] = 0.f;
#pragma unroll 1
  for (int u = 0; u < 64; u++) {
    if ((u & 7) == 0) mbar_wait(sb + SM_MBAR + MB_KV + (u >> 3) * 8, 0);
    wg_fence();
    qk(s, q, kb + tile_off(u));
    wg_commit();
    wg_wait<0>();
    fence_regs(s);
#pragma unroll
    for (int b = 0; b < 4; b++) {
      const float sc = ((PMASK >> ((u & 1) * 4 + b)) & 1) ? 0.5f : 1.f;
      m0 = fmaxf(m0, sc * fmaxf(s[4 * b], s[4 * b + 1]));
      m1 = fmaxf(m1, sc * fmaxf(s[4 * b + 2], s[4 * b + 3]));
    }
  }
  m0 = fmaxf(m0, __shfl_xor_sync(~0u, m0, 1)); m0 = fmaxf(m0, __shfl_xor_sync(~0u, m0, 2));
  m1 = fmaxf(m1, __shfl_xor_sync(~0u, m1, 1)); m1 = fmaxf(m1, __shfl_xor_sync(~0u, m1, 2));
#pragma unroll 1
  for (int u = 0; u < 64; u++) {
    wg_fence();
    qk(s, q, kb + tile_off(u));
    wg_commit();
    wg_wait<0>();
    fence_regs(s);
#pragma unroll
    for (int b = 0; b < 4; b++) {
      const float sc = ((PMASK >> ((u & 1) * 4 + b)) & 1) ? 0.5f : 1.f;
      p[2 * b] = pack_bf16(ex2(fmaf(s[4 * b], sc, -m0)), ex2(fmaf(s[4 * b + 1], sc, -m0)));
      p[2 * b + 1] = pack_bf16(ex2(fmaf(s[4 * b + 2], sc, -m1)), ex2(fmaf(s[4 * b + 3], sc, -m1)));
    }
    fence_regs(p);
    wg_fence();
    pv(o, p, kb + tile_off(u));
    wg_commit();
    wg_wait<0>();
    fence_regs(o); fence_regs(p);
  }
}

__device__ __forceinline__ uint32_t w_slot(int idx, int& goff) {
  const int k = idx / 9, nb = idx - k * 9;
  goff = k * DM + nb * 8;
  return nb * WNB + k * 16;
}
template <int BAR, int BN> __device__ __forceinline__ void ksplit_reduce(float (&res)[20], const float (&acc)[36], float* mine, const float* other, int d16, bool hi, int mh) {
#pragma unroll
  for (int i = 0; i < 20; i++) mine[i < 16 ? i * 128 : d16 + (i - 16) * 128] = hi ? acc[i] : acc[i < 16 ? 20 + i : 0];
  bar_sync(BN == 256 ? BAR + mh : BAR, BN);
#pragma unroll
  for (int i = 0; i < 20; i++) res[i] = (hi ? acc[i < 16 ? 20 + i : 0] : acc[i]) + other[i < 16 ? i * 128 : d16 + (i - 16) * 128];
}

__global__ void __launch_bounds__(NTHR, 1)
fused_kernel(const __grid_constant__ CUtensorMap xmap, const __nv_bfloat16* __restrict__ x, const __nv_bfloat16* __restrict__ wq,
             const __nv_bfloat16* __restrict__ wk, const __nv_bfloat16* __restrict__ wv, const __nv_bfloat16* __restrict__ wo,
             const __nv_bfloat16* __restrict__ w_r, const __nv_bfloat16* __restrict__ w_gate, const __nv_bfloat16* __restrict__ w_up,
             const __nv_bfloat16* __restrict__ w_down, const __nv_bfloat16* __restrict__ gate_w, __nv_bfloat16* __restrict__ out, uint32_t zero) {
  extern __shared__ __align__(1024) uint8_t smem[];
  const uint32_t sb = (uint32_t)__cvta_generic_to_shared(smem);
  const uint32_t mb = sb + SM_MBAR;
  TS(0);
  if (__any_sync(0xffffffffu, threadIdx.x >= 512)) {
    IDS
    unsigned tgt = 0;
    if (t128 == 0) {
#pragma unroll
      for (int i = 0; i < 21; i++) asm volatile("mbarrier.init.shared::cta.b64 [%0], 1;" ::"r"(mb + i * 8) : "memory");
      asm volatile("mbarrier.init.shared::cta.b64 [%0], 384;" ::"r"(mb + MB_W1) : "memory");
      asm volatile("mbarrier.init.shared::cta.b64 [%0], 128;" ::"r"(mb + MB_W3) : "memory");
      fence_async();
#pragma unroll
      for (int i = 0; i < 9; i++) {
        asm volatile("mbarrier.arrive.expect_tx.shared::cta.b64 _, [%0], 16384;" ::"r"(mb + MB_X + i * 8) : "memory");
        asm volatile("cp.async.bulk.tensor.2d.shared::cluster.global.mbarrier::complete_tx::bytes [%0], [%1, {%3, %4}], [%2];"
                     ::"r"(sb + i * 16384), "l"((uint64_t)&xmap), "r"(mb + MB_X + i * 8), "r"(i * 64), "r"(tb * 128) : "memory");
      }
      if (hg >= 6) tgt = ticket_arrive(&g_ctr[0], NCTA);
    }
    {
      const __nv_bfloat16* w = wq + hg * 72;
#pragma unroll
      for (int i = 0; i < 12; i++) { int go; uint32_t so = w_slot(tid - 256 + 384 * i, go); cp_async16(sb + SM_W1 + so, w + go); }
      uint4 lw[5];
#pragma unroll
      for (int i = 0; i < 5; i++) { int go; w_slot(4608 + t128 + 128 * i, go); if (t128 + 128 * i < 576) lw[i] = ldg_nc(w + go); }
      __syncthreads();
      if (hg < 6) bar_sync(8, 384);
#pragma unroll
      for (int i = 0; i < 5; i++) { int go; uint32_t so = w_slot(4608 + t128 + 128 * i, go); if (t128 + 128 * i < 576) *(uint4*)(smem + SM_W1 + so) = lw[i]; }
      cp_async_wait_all();
      fence_async();
      mbar_arrive(mb + MB_W1);
    }
    if (hg < 6) {
      bar_sync(3, 384);
      if (t128 == 0) tgt = ticket_arrive(&g_ctr[0], NCTA);
    }
    if (t128 == 0) {
      prefetch_l2((const uint8_t*)w_gate + bid * 41472, 41472);
      prefetch_l2((const uint8_t*)w_up + bid * 41472, 41472);
      prefetch_l2((const uint8_t*)w_down + bid * 41472, 41472);
      prefetch_l2((const uint8_t*)wo + bid * 5184, 5184);
      ticket_wait(&g_ctr[0], tgt);
      fence_async_g();
      TS2(5);
    }
    bar_sync(9, NTHR);
    if (t128 == 0) {
#pragma unroll
      for (int i = 0; i < 8; i++) bulk_load(sb + i * 24576, (const uint8_t*)g_kv + i * 24576, 24576, mb + MB_KV + i * 8);
    }
    if (wi == 1) {
      float kmax = 0.f;
#pragma unroll
      for (int i = 0; i < 4; i++) { float4 v = __ldcg(&g_kn[lane + 32 * i]); kmax = fmaxf(kmax, v.x + v.y + v.z); }
#pragma unroll
      for (int o = 1; o < 32; o <<= 1) kmax = fmaxf(kmax, __shfl_xor_sync(~0u, kmax, o));
      if (lane == 0) *(volatile float*)(smem + SM_MISC + 292) = kmax;
      __syncwarp();
      bar_arrive(11, 544);
    }
    unsigned long long best = 0ull;
#pragma unroll
    for (int i = 0; i < 4; i++) { unsigned long long b2 = __ldcg(&g_best[lane + 32 * i]); best = b2 > best ? b2 : best; }
#pragma unroll
    for (int o = 1; o < 32; o <<= 1) { unsigned long long b2 = __shfl_xor_sync(~0u, best, o); best = b2 > best ? b2 : best; }
    const int sel = (int)(~(uint32_t)best) & (S_LEN - 1);
    uint32_t rb = (uint32_t)(best >> 32);
    rb = (rb & 0x80000000u) ? (rb & 0x7FFFFFFFu) : ~rb;
    const float rsel = rbf(sigmoidf_(__uint_as_float(rb)));
    float* xs = (float*)(smem + SM_SV);
    float* m1 = xs + 576;
    float* hs = m1 + 864;
    if (t128 < 72) {
      uint4 v = ldg_nc(x + (size_t)sel * DM + t128 * 8);
      *(float4*)(xs + t128 * 8) = make_float4(bf_lo(v.x), bf_hi(v.x), bf_lo(v.y), bf_hi(v.y));
      *(float4*)(xs + t128 * 8 + 4) = make_float4(bf_lo(v.z), bf_hi(v.z), bf_lo(v.w), bf_hi(v.w));
    }
    bar_sync(13, 128);
    if (t128 < 108) {
      const int rg = t128 / 9, q9 = t128 - rg * 9;
      float ga[4] = {0.f, 0.f, 0.f, 0.f}, ua[4] = {0.f, 0.f, 0.f, 0.f};
#pragma unroll 1
      for (int b = 0; b < 4; b++) {
        uint2 wgv[12], wuv[12];
#pragma unroll
        for (int i = 0; i < 12; i++) {
          const size_t off = (size_t)(rg + 12 * (b * 12 + i)) * FF + bid * 36 + q9 * 4;
          wgv[i] = ldg_nc2(w_gate + off); wuv[i] = ldg_nc2(w_up + off);
        }
#pragma unroll
        for (int i = 0; i < 12; i++) {
          const float xv = xs[rg + 12 * (b * 12 + i)];
          ga[0] = fmaf(xv, bf_lo(wgv[i].x), ga[0]); ga[1] = fmaf(xv, bf_hi(wgv[i].x), ga[1]);
          ga[2] = fmaf(xv, bf_lo(wgv[i].y), ga[2]); ga[3] = fmaf(xv, bf_hi(wgv[i].y), ga[3]);
          ua[0] = fmaf(xv, bf_lo(wuv[i].x), ua[0]); ua[1] = fmaf(xv, bf_hi(wuv[i].x), ua[1]);
          ua[2] = fmaf(xv, bf_lo(wuv[i].y), ua[2]); ua[3] = fmaf(xv, bf_hi(wuv[i].y), ua[3]);
        }
      }
      *(float4*)(m1 + rg * 72 + q9 * 4) = make_float4(ga[0], ga[1], ga[2], ga[3]);
      *(float4*)(m1 + rg * 72 + 36 + q9 * 4) = make_float4(ua[0], ua[1], ua[2], ua[3]);
    }
    bar_sync(13, 128);
    if (t128 < 36) {
      float gs = 0.f, us = 0.f;
#pragma unroll
      for (int i = 0; i < 12; i++) { gs += m1[i * 72 + t128]; us += m1[i * 72 + 36 + t128]; }
      gs = rbf(gs); us = rbf(us);
      hs[t128] = rbf(rbf(gs * sigmoidf_(gs)) * us);
    }
    bar_sync(13, 128);
    if (t128 < 72) {
      float y[8] = {0.f, 0.f, 0.f, 0.f, 0.f, 0.f, 0.f, 0.f};
#pragma unroll 1
      for (int b = 0; b < 3; b++) {
        uint4 wd[12];
#pragma unroll
        for (int i = 0; i < 12; i++) wd[i] = ldg_nc(w_down + (size_t)(bid * 36 + b * 12 + i) * DM + t128 * 8);
#pragma unroll
        for (int i = 0; i < 12; i++) {
          const float hv = hs[b * 12 + i];
          y[0] = fmaf(hv, bf_lo(wd[i].x), y[0]); y[1] = fmaf(hv, bf_hi(wd[i].x), y[1]);
          y[2] = fmaf(hv, bf_lo(wd[i].y), y[2]); y[3] = fmaf(hv, bf_hi(wd[i].y), y[3]);
          y[4] = fmaf(hv, bf_lo(wd[i].z), y[4]); y[5] = fmaf(hv, bf_hi(wd[i].z), y[5]);
          y[6] = fmaf(hv, bf_lo(wd[i].w), y[6]); y[7] = fmaf(hv, bf_hi(wd[i].w), y[7]);
        }
      }
      *(float4*)(g_ypart + bid * DM + t128 * 8) = make_float4(y[0], y[1], y[2], y[3]);
      *(float4*)(g_ypart + bid * DM + t128 * 8 + 4) = make_float4(y[4], y[5], y[6], y[7]);
    }
    bar_sync(13, 128);
    if (t128 == 0) { tgt = ticket_arrive(&g_ctr[32 * 17], NCTA); *(volatile int*)(smem + SM_MISC + 288) = sel; }
    TS2(10);
    if ((sel >> 7) == tb) {
      if (t128 == 0) ticket_wait(&g_ctr[32 * 17], tgt);
      bar_sync(13, 128);
      if (t128 < 72) {
        float s0 = 0.f, s1 = 0.f, s2 = 0.f, s3 = 0.f;
        const float* yp = g_ypart + hg * 72 + t128;
#pragma unroll 4
        for (int i = 0; i < 32; i++) {
          s0 += __ldcg(yp + i * DM); s1 += __ldcg(yp + (32 + i) * DM); s2 += __ldcg(yp + (64 + i) * DM); s3 += __ldcg(yp + (96 + i) * DM);
        }
        ((float*)(smem + SM_MISC))[t128] = rbf(rbf((s0 + s1) + (s2 + s3)) * rsel);
      }
    }
    bar_sync(10, NTHR);
    {
      const __nv_bfloat16* w = wo + hg * 72;
#pragma unroll 4
      for (int i = 0; i < 41; i++) {
        const int idx = t128 + 128 * i;
        if (idx < 5184) { int go; uint32_t so = w_slot(idx, go); cp_async16(sb + SM_W3 + so, w + go); }
      }
      cp_async_wait_all();
      fence_async();
      mbar_arrive(mb + MB_W3);
    }
    TS2(15);
    bar_sync(12, NTHR);
    if (t128 == 0) {
      tgt = ticket_arrive(&g_ctr[32 * (1 + tb)], 8);
      ticket_wait(&g_ctr[32 * (1 + tb)], tgt);
      fence_async_g();
      TS2(11);
#pragma unroll
      for (int i = 0; i < 4; i++) bulk_load(sb + SM_O + i * 36864, (const uint8_t*)g_o + tb * 147456 + i * 36864, 36864, mb + MB_O + i * 8);
    }
    return;
  }

  {
  IDS
  const bool khu = __any_sync(0xffffffffu, kh != 0);
  if (khu) {
    const __nv_bfloat16* w = wq + hg * 72;
#pragma unroll
    for (int i = 0; i < 12; i++) { int go; uint32_t so = w_slot(tid - 256 + 384 * i, go); cp_async16(sb + SM_W1 + so, w + go); }
  } else if (hg < 6) {
    uint4 ev[3];
#pragma unroll
    for (int i = 0; i < 3; i++) {
      const int k = tid + 256 * i;
      ev[i] = make_uint4(0, 0, 0, 0);
      if (k < DM) {
        const uint32_t* src = (const uint32_t*)((hg < 3 ? wk : wv) + k * 18) + (hg % 3) * 4;
        ev[i].x = __ldg(src);
        if (hg % 3 != 2) { ev[i].y = __ldg(src + 1); ev[i].z = __ldg(src + 2); ev[i].w = __ldg(src + 3); }
        else if (hg == 2) ev[i].y = (uint32_t)__bfloat16_as_ushort(w_r[k]) | ((uint32_t)__bfloat16_as_ushort(gate_w[k]) << 16);
      }
    }
#pragma unroll
    for (int i = 0; i < 3; i++) {
      const int k = tid + 256 * i;
      if (k < DM) *(uint4*)(smem + SM_W1 + (k >> 6) * WNB + 8192 + (k & 63) * 16) = ev[i];
    }
    fence_async();
  }
  __syncthreads();
  const uint64_t ad = make_desc(sb + mh * 8192, 16, 1024) | (1ull << 62);
  if (khu) {
    cp_async_wait_all();
    fence_async();
    mbar_arrive(mb + MB_W1);
  } else if (hg < 6) {
    float e[4] = {0.f, 0.f, 0.f, 0.f};
    const uint64_t ed = make_desc(sb + SM_W1 + 8192, 128, 128);
#pragma unroll 1
    for (int b = 0; b < 9; b++) {
      mbar_wait(mb + MB_X + b * 8, 0);
      wg_fence();
#pragma unroll
      for (int j = 0; j < 4; j++) wgmma_t(e, ad + (uint64_t)(b * 1024 + j * 2), ed + (uint64_t)(b * (WNB / 16) + j * 16), 1);
      wg_commit();
    }
    wg_wait<0>();
    fence_regs(e);
    bar_arrive(8, 384);
    TS(1);
    const int ch = hg % 3;
    float nrm = 0.f;
    unsigned long long best = 0ull;
#pragma unroll
    for (int h = 0; h < 2; h++) {
      const int key = tb * 128 + lrow + 8 * h;
      const bool poly = (PMASK >> ((key >> 3) & 7)) & 1;
      uint32_t v = pack_bf16(e[2 * h], e[2 * h + 1]);
      if (hg < 3) {
        float lo = bf_lo(v), hi = bf_hi(v);
        float n2 = (hg == 2 && c != 0) ? 0.f : lo * lo + hi * hi;
        n2 += __shfl_xor_sync(~0u, n2, 1);
        n2 += __shfl_xor_sync(~0u, n2, 2);
        nrm = fmaxf(nrm, n2);
        if (hg == 2 && c == 1) {
          g_gate[key] = rbf(sigmoidf_(hi));
          uint32_t rb = __float_as_uint(lo);
          rb = (rb & 0x80000000u) ? ~rb : (rb | 0x80000000u);
          unsigned long long cand = ((unsigned long long)rb << 32) | (uint32_t)(~key);
          best = cand > best ? cand : best;
        }
        if (poly) v = pack_bf16(2.f * lo, 2.f * hi);
        if (hg == 2 && c != 0) v = c == 1 ? (poly ? 0x44404000u : 0x00003F80u) : (c == 2 && poly ? 0x0000BFFFu : 0u);
      } else if (hg == 5 && c != 0) {
        v = c == 1 ? 0x00003F80u : 0u;
      }
      uint8_t* dst = (uint8_t*)g_kv + (key >> 8) * 24576 + (hg >= 3 ? 12288 : 0) + ((key >> 3) & 31) * 384 + ch * 128 + (key & 7) * 16 + c * 4;
      *(uint32_t*)dst = v;
    }
    if (hg < 3) {
#pragma unroll
      for (int o = 4; o < 32; o <<= 1) nrm = fmaxf(nrm, __shfl_xor_sync(~0u, nrm, o));
      if (lane == 0) ((float*)&g_kn[tb * 8 + mh * 4 + wi])[hg] = nrm;
      if (hg == 2) {
#pragma unroll
        for (int o = 1; o < 32; o <<= 1) { unsigned long long b2 = __shfl_xor_sync(~0u, best, o); best = b2 > best ? b2 : best; }
        if (lane == 0) g_best[tb * 8 + mh * 4 + wi] = best;
      }
    }
    fence_async_g();
    bar_arrive(3, 384);
    TS(2);
  }
  {
    float acc0[36], acc[20];
#pragma unroll
    for (int j = 0; j < 36; j++) acc0[j] = 0.f;
    mbar_wait(mb + MB_W1, 0);
#pragma unroll 1
    for (int b = 0; b < 5; b++) mbar_wait(mb + MB_X + ((khu ? 4 : 0) + b) * 8, 0);
    TS(3);
    const uint64_t wd = make_desc(sb + SM_W1 + (khu ? 4608 : 0), 128, WNB);
    const int k0 = khu ? 18 : 0;
    wg_fence();
#pragma unroll
    for (int j = 0; j < 18; j++) wgmma_t(acc0, ad + (uint64_t)(((k0 + j) >> 2) * 1024 + ((k0 + j) & 3) * 2), wd + (uint64_t)(j * 16), 1);
    wg_commit();
    wg_wait<0>();
    fence_regs(acc0);
    ksplit_reduce<14, 512>(acc, acc0, (float*)(smem + (khu ? 7 : 0) * 16384 + mh * 8192) + t128, (const float*)(smem + (khu ? 0 : 7) * 16384 + mh * 8192) + t128,
                           4096, khu, mh);
    const float qs = 0.23570226039551584f * 1.4426950408889634f;
    uint8_t* qp = smem + SM_Q + lrow * 144 + kh * 80 + c * 4;
#pragma unroll
    for (int nb = 0; nb < 5; nb++) {
      if (nb < 4 || kh == 0) {
        *(uint32_t*)(qp + nb * 16) = pack_bf16(acc[4 * nb] * qs, acc[4 * nb + 1] * qs);
        *(uint32_t*)(qp + 8 * 144 + nb * 16) = pack_bf16(acc[4 * nb + 2] * qs, acc[4 * nb + 3] * qs);
      }
    }
  }
  fence_async();
  TS(4);
  bar_sync(9, NTHR);
  }
  {
    PC pc; pc.msk = 0x007F007Fu + zero; pc.cb = 0x3DCD3DCDu + zero;
#pragma unroll 1
    for (int pass = 0; pass < 2; pass++) {
      uint32_t q[8];
      uint32_t unsafe;
      {
      IDS
      const int r0 = pass * 64 + wi * 16 + g;
      const uint8_t* qp = smem + SM_Q + r0 * 144 + wg * 36 + c * 4;
      q[0] = *(const uint32_t*)qp; q[1] = *(const uint32_t*)(qp + 8 * 144);
      q[2] = *(const uint32_t*)(qp + 16); q[3] = *(const uint32_t*)(qp + 8 * 144 + 16);
      q[4] = c == 0 ? *(const uint32_t*)(qp + 32) : 0u; q[5] = c == 0 ? *(const uint32_t*)(qp + 8 * 144 + 32) : 0u;
      float n0 = bf_lo(q[0]) * bf_lo(q[0]) + bf_hi(q[0]) * bf_hi(q[0]) + bf_lo(q[2]) * bf_lo(q[2]) + bf_hi(q[2]) * bf_hi(q[2]) + bf_lo(q[4]) * bf_lo(q[4]) + bf_hi(q[4]) * bf_hi(q[4]);
      float n1 = bf_lo(q[1]) * bf_lo(q[1]) + bf_hi(q[1]) * bf_hi(q[1]) + bf_lo(q[3]) * bf_lo(q[3]) + bf_hi(q[3]) * bf_hi(q[3]) + bf_lo(q[5]) * bf_lo(q[5]) + bf_hi(q[5]) * bf_hi(q[5]);
      n0 += __shfl_xor_sync(~0u, n0, 1); n0 += __shfl_xor_sync(~0u, n0, 2);
      n1 += __shfl_xor_sync(~0u, n1, 1); n1 += __shfl_xor_sync(~0u, n1, 2);
      if (pass == 0) bar_sync(11, 544);
      const float kmax = *(volatile float*)(smem + SM_MISC + 292);
      const float m0 = ceilf(sqrtf(n0 * kmax) * 1.001f + 0.01f), m1 = ceilf(sqrtf(n1 * kmax) * 1.001f + 0.01f);
      asm volatile("{\n.reg .pred p, r;\nsetp.ne.u32 p, %1, 0;\nbarrier.cta.red.or.pred.aligned r, %2, 128, p;\nselp.u32 %0, 1, 0, r;\n}\n"
                   : "=r"(unsafe) : "r"((uint32_t)!(m0 <= 60.f && m1 <= 60.f)), "r"(4 + wg) : "memory");
      q[6] = unsafe ? 0u : c == 1 ? pack_bf16(-m0, 1.f) : c == 2 ? 0x3F803F80u : 0u;
      q[7] = unsafe ? 0u : c == 1 ? pack_bf16(-m1, 1.f) : c == 2 ? 0x3F803F80u : 0u;
      }
      float o[12];
      TS(6 + pass);
      if (!__any_sync(0xffffffffu, unsafe)) {
        attn_fast(q, o, sb, pc, pass == 1 ? 5 : -1);
      } else {
        attn_safe(q, o, sb);
        if (pass == 1) bar_arrive(10, NTHR);
      }
      IDS
      const float i0 = 1.f / __shfl_sync(~0u, o[8], (lane & ~3) | 1), i1 = 1.f / __shfl_sync(~0u, o[10], (lane & ~3) | 1);
      uint8_t* ob = (uint8_t*)g_o + tb * 147456 + (pass + 2 * (hg >> 2)) * 36864 + wi * 9216 + g * 16;
      const int c0 = (hg & 3) * 72 + wg * 18 + 2 * c;
      uint8_t* p0 = ob + (c0 >> 3) * 128 + (c0 & 7) * 2;
      *(uint32_t*)p0 = pack_bf16(o[0] * i0, o[1] * i0); *(uint32_t*)(p0 + 4608) = pack_bf16(o[2] * i1, o[3] * i1);
      *(uint32_t*)(p0 + 128) = pack_bf16(o[4] * i0, o[5] * i0); *(uint32_t*)(p0 + 4608 + 128) = pack_bf16(o[6] * i1, o[7] * i1);
      if (c == 0) { *(uint32_t*)(p0 + 256) = pack_bf16(o[8] * i0, o[9] * i0); *(uint32_t*)(p0 + 4608 + 256) = pack_bf16(o[10] * i1, o[11] * i1); }
    }
  }
  TS(8);
  fence_async_g();
  bar_arrive(12, NTHR);

  {
    IDS
    const bool khu = __any_sync(0xffffffffu, kh != 0);
    const int row = tb * 128 + lrow;
    const int nb0 = kh == 0 ? 0 : 5;
    uint32_t xr[10];
    {
      const uint32_t* xp = (const uint32_t*)(x + (size_t)row * DM + hg * 72 + nb0 * 8) + c;
#pragma unroll
      for (int i = 0; i < 5; i++) {
        xr[2 * i] = (i < 4 || kh == 0) ? __ldg(xp + i * 4) : 0u;
        xr[2 * i + 1] = (i < 4 || kh == 0) ? __ldg(xp + 4 * DM + i * 4) : 0u;
      }
    }
    const float g0 = __ldcg(&g_gate[row]), g1 = __ldcg(&g_gate[row + 8]);
    float acc0[36], acc[20];
    {
      const uint64_t ad = make_desc(sb + SM_O + wg * 36864, 128, 4608), wd = make_desc(sb + SM_W3 + (khu ? 4608 : 0), 128, WNB);
#pragma unroll
      for (int j = 0; j < 36; j++) acc0[j] = 0.f;
      mbar_wait(mb + MB_W3, 0);
      mbar_wait(mb + MB_O + wg * 8, 0);
      TS(12);
      wg_fence();
#pragma unroll
      for (int j = 0; j < 18; j++) wgmma_t(acc0, ad + (uint64_t)(j * 16), wd + (uint64_t)(j * 16), 1);
      wg_commit();
      wg_wait<0>();
      fence_regs(acc0);
    }
    ksplit_reduce<1, 256>(acc, acc0, (float*)(smem + SM_O + wg * 36864) + t128, (const float*)(smem + SM_O + (wg ^ 2) * 36864) + t128, 2048, khu, mh);
    TS(13);
    const float* upd = (const float*)(smem + SM_MISC);
    const int sel = *(volatile int*)(smem + SM_MISC + 288);
    const float h0 = rbf(1.f - g0), h1 = rbf(1.f - g1);
    uint32_t* op = (uint32_t*)(out + (size_t)row * DM + hg * 72 + nb0 * 8) + c;
#pragma unroll
    for (int i = 0; i < 5; i++) {
      if (i < 4 || kh == 0) {
        const float a0 = acc[4 * i], a1 = acc[4 * i + 1], a2 = acc[4 * i + 2], a3 = acc[4 * i + 3];
        const uint32_t x0 = xr[2 * i], x1 = xr[2 * i + 1];
        float b0 = bf_lo(x0), b1 = bf_hi(x0), b2 = bf_lo(x1), b3 = bf_hi(x1);
        const int col = (nb0 + i) * 8 + c * 2;
        if (row == sel) { b0 = rbf(b0 + upd[col]); b1 = rbf(b1 + upd[col + 1]); }
        if (row + 8 == sel) { b2 = rbf(b2 + upd[col]); b3 = rbf(b3 + upd[col + 1]); }
        op[i * 4] = pack_bf16(rbf(g0 * rbf(a0)) + rbf(h0 * b0), rbf(g0 * rbf(a1)) + rbf(h0 * b1));
        op[4 * DM + i * 4] = pack_bf16(rbf(g1 * rbf(a2)) + rbf(h1 * b2), rbf(g1 * rbf(a3)) + rbf(h1 * b3));
      }
    }
    TS(14);
  }
}

typedef CUresult (*EncodeFn)(CUtensorMap*, CUtensorMapDataType, cuuint32_t, void*, const cuuint64_t*, const cuuint64_t*, const cuuint32_t*,
                             const cuuint32_t*, CUtensorMapInterleave, CUtensorMapSwizzle, CUtensorMapL2promotion, CUtensorMapFloatOOBfill);

extern "C" void kernel_launch(void* const* d_in, const int* in_sizes, int n_in, void* d_out, int out_size) {
  static EncodeFn enc = nullptr;
  if (!enc) {
    cudaDriverEntryPointQueryResult qr;
    void* fn = nullptr;
    cudaGetDriverEntryPoint("cuTensorMapEncodeTiled", &fn, cudaEnableDefault, &qr);
    enc = (EncodeFn)fn;
    cudaFuncSetAttribute(fused_kernel, cudaFuncAttributeMaxDynamicSharedMemorySize, SM_TOTAL);
  }
  CUtensorMap xmap;
  const cuuint64_t gdim[2] = {DM, S_LEN}, gstr[1] = {DM * 2};
  const cuuint32_t box[2] = {64, 128}, estr[2] = {1, 1};
  enc(&xmap, CU_TENSOR_MAP_DATA_TYPE_BFLOAT16, 2, d_in[0], gdim, gstr, box, estr, CU_TENSOR_MAP_INTERLEAVE_NONE, CU_TENSOR_MAP_SWIZZLE_128B,
      CU_TENSOR_MAP_L2_PROMOTION_L2_128B, CU_TENSOR_MAP_FLOAT_OOB_FILL_NONE);
  typedef const __nv_bfloat16* P;
  fused_kernel<<<NCTA, NTHR, SM_TOTAL, cudaStreamPerThread>>>(xmap, (P)d_in[0], (P)d_in[1], (P)d_in[2], (P)d_in[3], (P)d_in[4], (P)d_in[6],
                                                             (P)d_in[7], (P)d_in[8], (P)d_in[9], (P)d_in[10], (__nv_bfloat16*)d_out, 0u);
}
```

```cpp
#include <cuda_runtime.h>
#include <cuda.h>
#include <cuda_bf16.h>
#include <stdint.h>

#define S_LEN 2048
#define DM 576
#define FF 4608
#define NCTA 128
#define PMASK 0xB5u

__device__ uint4 g_kv[8 * 1536];
__device__ float4 g_kn[128];
__device__ unsigned long long g_best[128];
__device__ float g_gate[S_LEN];
__device__ uint4 g_o[S_LEN * DM / 8];
__device__ float g_ypart[NCTA * DM];
__device__ unsigned g_ctr[32 * 32];

#define TS(k)
#define TS2(k)
#define WNB 9232
#define SM_W1 147456
#define SM_Q 196608
#define SM_SV 221184
#define SM_W3 0
#define SM_O 83200
#define SM_MBAR 230656
#define MB_X 0
#define MB_KV 72
#define MB_O 136
#define MB_W1 168
#define MB_W3 176
#define SM_MISC 230912
#define SM_TOTAL 231424
#define NTHR 640

__device__ __forceinline__ uint64_t make_desc(uint32_t saddr, uint32_t lbo, uint32_t sbo) {
  return (uint64_t)((saddr & 0x3FFFF) >> 4) | ((uint64_t)(lbo >> 4) << 16) | ((uint64_t)(sbo >> 4) << 32);
}
__device__ __forceinline__ void wg_fence() { asm volatile("wgmma.fence.sync.aligned;" ::: "memory"); }
__device__ __forceinline__ void wg_commit() { asm volatile("wgmma.commit_group.sync.aligned;" ::: "memory"); }
template <int N> __device__ __forceinline__ void wg_wait() { asm volatile("wgmma.wait_group.sync.aligned %0;" ::"n"(N) : "memory"); }
__device__ __forceinline__ void wgmma_t(float (&d)[4], uint64_t da, uint64_t db, int sd) {
  asm volatile("{\n.reg .pred p;\nsetp.ne.b32 p, %6, 0;\n"
    "wgmma.mma_async.sync.aligned.m64n8k16.f32.bf16.bf16 "
    "{%0,%1,%2,%3}, %4, %5, p, 1, 1, 0, 1;\n}\n"
    : "+f"(d[0]),"+f"(d[1]),"+f"(d[2]),"+f"(d[3])
    : "l"(da),"l"(db),"r"(sd));
}
__device__ __forceinline__ void wgmma_t(float (&d)[36], uint64_t da, uint64_t db, int sd) {
  asm volatile("{\n.reg .pred p;\nsetp.ne.b32 p, %38, 0;\n"
    "wgmma.mma_async.sync.aligned.m64n72k16.f32.bf16.bf16 "
    "{%0,%1,%2,%3,%4,%5,%6,%7,%8,%9,%10,%11,%12,%13,%14,%15,%16,%17,%18,%19,%20,%21,%22,%23,%24,%25,%26,%27,%28,%29,%30,%31,%32,%33,%34,%35}, %36, %37, p, 1, 1, 0, 1;\n}\n"
    : "+f"(d[0]),"+f"(d[1]),"+f"(d[2]),"+f"(d[3]),"+f"(d[4]),"+f"(d[5]),"+f"(d[6]),"+f"(d[7]),"+f"(d[8]),"+f"(d[9]),"+f"(d[10]),"+f"(d[11]),"+f"(d[12]),"+f"(d[13]),"+f"(d[14]),"+f"(d[15]),"+f"(d[16]),"+f"(d[17]),"+f"(d[18]),"+f"(d[19]),"+f"(d[20]),"+f"(d[21]),"+f"(d[22]),"+f"(d[23]),"+f"(d[24]),"+f"(d[25]),"+f"(d[26]),"+f"(d[27]),"+f"(d[28]),"+f"(d[29]),"+f"(d[30]),"+f"(d[31]),"+f"(d[32]),"+f"(d[33]),"+f"(d[34]),"+f"(d[35])
    : "l"(da),"l"(db),"r"(sd));
}
template <int SD> __device__ __forceinline__ void wg_qk(float (&d)[32], uint64_t da, uint64_t db) {
  asm volatile("{\n.reg .pred p;\nsetp.ne.b32 p, %34, 0;\n"
    "wgmma.mma_async.sync.aligned.m64n64k16.f32.bf16.bf16 "
    "{%0,%1,%2,%3,%4,%5,%6,%7,%8,%9,%10,%11,%12,%13,%14,%15,%16,%17,%18,%19,%20,%21,%22,%23,%24,%25,%26,%27,%28,%29,%30,%31}, %32, %33, p, 1, 1, 0, 0;\n}\n"
    : "+f"(d[0]),"+f"(d[1]),"+f"(d[2]),"+f"(d[3]),"+f"(d[4]),"+f"(d[5]),"+f"(d[6]),"+f"(d[7]),"+f"(d[8]),"+f"(d[9]),"+f"(d[10]),"+f"(d[11]),"+f"(d[12]),"+f"(d[13]),"+f"(d[14]),"+f"(d[15]),"+f"(d[16]),"+f"(d[17]),"+f"(d[18]),"+f"(d[19]),"+f"(d[20]),"+f"(d[21]),"+f"(d[22]),"+f"(d[23]),"+f"(d[24]),"+f"(d[25]),"+f"(d[26]),"+f"(d[27]),"+f"(d[28]),"+f"(d[29]),"+f"(d[30]),"+f"(d[31])
    : "l"(da),"l"(db),"n"(SD));
}
__device__ __forceinline__ void wg_pv(float (&d)[12], uint32_t a0, uint32_t a1, uint32_t a2, uint32_t a3, uint64_t db) {
  asm volatile("wgmma.mma_async.sync.aligned.m64n24k16.f32.bf16.bf16 "
    "{%0,%1,%2,%3,%4,%5,%6,%7,%8,%9,%10,%11}, {%12,%13,%14,%15}, %16, 1, 1, 1, 1;\n"
    : "+f"(d[0]),"+f"(d[1]),"+f"(d[2]),"+f"(d[3]),"+f"(d[4]),"+f"(d[5]),"+f"(d[6]),"+f"(d[7]),"+f"(d[8]),"+f"(d[9]),"+f"(d[10]),"+f"(d[11])
    : "r"(a0),"r"(a1),"r"(a2),"r"(a3),"l"(db));
}
template <int N> __device__ __forceinline__ void fence_regs(float (&s)[N]) {
#pragma unroll
  for (int i = 0; i < N; i++) asm volatile("" : "+f"(s[i])::"memory");
}
template <int N> __device__ __forceinline__ void fence_regs(uint32_t (&s)[N]) {
#pragma unroll
  for (int i = 0; i < N; i++) asm volatile("" : "+r"(s[i])::"memory");
}
__device__ __forceinline__ float ex2(float x) { float r; asm("ex2.approx.ftz.f32 %0, %1;" : "=f"(r) : "f"(x)); return r; }
__device__ __forceinline__ uint32_t pack_bf16(float lo, float hi) { uint32_t r; asm("cvt.rn.bf16x2.f32 %0, %1, %2;" : "=r"(r) : "f"(hi), "f"(lo)); return r; }
__device__ __forceinline__ float bf_lo(uint32_t v) { return __uint_as_float(v << 16); }
__device__ __forceinline__ float bf_hi(uint32_t v) { return __uint_as_float(v & 0xFFFF0000u); }
__device__ __forceinline__ float rbf(float x) { return __uint_as_float(pack_bf16(0.f, x)); }
__device__ __forceinline__ uint32_t hfma2(uint32_t a, uint32_t b, uint32_t c) { uint32_t r; asm("fma.rn.bf16x2 %0, %1, %2, %3;" : "=r"(r) : "r"(a), "r"(b), "r"(c)); return r; }
template <int LUT> __device__ __forceinline__ uint32_t lop3(uint32_t a, uint32_t b, uint32_t c) { uint32_t r; asm("lop3.b32 %0, %1, %2, %3, %4;" : "=r"(r) : "r"(a), "r"(b), "r"(c), "n"(LUT)); return r; }
__device__ __forceinline__ float sigmoidf_(float x) { return 1.f / (1.f + __expf(-x)); }
__device__ __forceinline__ void bar_sync(int id, int n) { asm volatile("bar.sync %0, %1;" ::"r"(id), "r"(n) : "memory"); }
__device__ __forceinline__ void bar_arrive(int id, int n) { asm volatile("bar.arrive %0, %1;" ::"r"(id), "r"(n) : "memory"); }
__device__ __forceinline__ void mbar_arrive(uint32_t bar) { asm volatile("mbarrier.arrive.shared::cta.b64 _, [%0];" ::"r"(bar) : "memory"); }
__device__ __forceinline__ void bulk_load(uint32_t dst, const void* src, uint32_t bytes, uint32_t bar) {
  asm volatile("mbarrier.arrive.expect_tx.shared::cta.b64 _, [%0], %1;" ::"r"(bar), "r"(bytes) : "memory");
  asm volatile("cp.async.bulk.shared::cluster.global.mbarrier::complete_tx::bytes [%0], [%1], %2, [%3];" ::"r"(dst), "l"(src), "r"(bytes), "r"(bar) : "memory");
}
__device__ __forceinline__ void fence_async() { asm volatile("fence.proxy.async.shared::cta;" ::: "memory"); }
__device__ __forceinline__ void fence_async_g() { asm volatile("fence.proxy.async.global;" ::: "memory"); }
__device__ __forceinline__ void cp_async16(uint32_t dst, const void* src) { asm volatile("cp.async.cg.shared.global [%0], [%1], 16;" ::"r"(dst), "l"(src) : "memory"); }
__device__ __forceinline__ void cp_async_wait_all() { asm volatile("cp.async.wait_all;" ::: "memory"); }
__device__ __forceinline__ uint4 ldg_nc(const void* p) { uint4 v; asm volatile("ld.global.nc.L1::no_allocate.v4.u32 {%0,%1,%2,%3}, [%4];" : "=r"(v.x), "=r"(v.y), "=r"(v.z), "=r"(v.w) : "l"(p)); return v; }
__device__ __forceinline__ uint2 ldg_nc2(const void* p) { uint2 v; asm volatile("ld.global.nc.L1::no_allocate.v2.u32 {%0,%1}, [%2];" : "=r"(v.x), "=r"(v.y) : "l"(p)); return v; }
__device__ __forceinline__ uint4 ldg_cg(const void* p) { uint4 v; asm volatile("ld.global.cg.v4.u32 {%0,%1,%2,%3}, [%4];" : "=r"(v.x), "=r"(v.y), "=r"(v.z), "=r"(v.w) : "l"(p) : "memory"); return v; }
__device__ __forceinline__ void prefetch_l2(const void* p, uint32_t bytes) { asm volatile("cp.async.bulk.prefetch.L2.global [%0], %1;" ::"l"(p), "r"(bytes) : "memory"); }

__device__ __forceinline__ int fresh_tid() { int t; asm volatile("mov.u32 %0, %%tid.x;" : "=r"(t)); return t; }
__device__ __forceinline__ int fresh_bid() { int t; asm volatile("mov.u32 %0, %%ctaid.x;" : "=r"(t)); return t; }
#define IDS                                                                                                          \
  const int tid = fresh_tid(), wg = tid >> 7, wi = (tid >> 5) & 3, lane = tid & 31, g = lane >> 2, c = lane & 3;     \
  const int bid = fresh_bid(), tb = bid >> 3, hg = bid & 7, mh = wg & 1, kh = wg >> 1, t128 = tid & 127;             \
  const int lrow = mh * 64 + wi * 16 + g;                                                                            \
  (void)wi; (void)g; (void)c; (void)tb; (void)hg; (void)mh; (void)kh; (void)t128; (void)lrow; (void)lane;
__device__ __forceinline__ unsigned ticket_arrive(unsigned* ctr, unsigned n) {
  unsigned old;
  asm volatile("atom.add.release.gpu.global.u32 %0, [%1], 1;" : "=r"(old) : "l"(ctr) : "memory");
  return (old / n + 1) * n;
}
__device__ __forceinline__ void ticket_wait(unsigned* ctr, unsigned target) {
  for (int it = 0; it < (1 << 22); it++) {
    unsigned v;
    asm volatile("ld.acquire.gpu.global.u32 %0, [%1];" : "=r"(v) : "l"(ctr) : "memory");
    if ((int)(v - target) >= 0) break;
  }
}
__device__ __forceinline__ void mbar_wait(uint32_t bar, uint32_t parity) {
  for (int it = 0; it < (1 << 20); it++) {
    uint32_t ok;
    asm volatile("{\n.reg .pred p;\nmbarrier.try_wait.parity.shared::cta.b64 p, [%1], %2;\nselp.u32 %0, 1, 0, p;\n}\n" : "=r"(ok) : "r"(bar), "r"(parity) : "memory");
    if (__all_sync(0xffffffffu, ok)) break;
  }
}

struct PC { uint32_t msk, cb; };
__device__ __forceinline__ uint32_t exp2_sw(float u0, float u1, const PC& pc) {
  uint32_t w = __byte_perm(__float_as_uint(u0), __float_as_uint(u1), 0x6521);
  uint32_t g = lop3<0xEC>(w, 0x3F803F80u, pc.msk);
  uint32_t k = hfma2(g, pc.cb, 0xBF34BF34u);
  uint32_t d = hfma2(k, k, 0xBD6BBD6Bu);
  return hfma2(w, d, w);
}
__device__ __forceinline__ void softmax64(const float (&s)[32], uint32_t (&p)[16], const PC& pc) {
#pragma unroll
  for (int i = 0; i < 8; i++) {
    if ((PMASK >> i) & 1) {
      p[2 * i] = exp2_sw(s[4 * i], s[4 * i + 1], pc);
      p[2 * i + 1] = exp2_sw(s[4 * i + 2], s[4 * i + 3], pc);
    } else {
      p[2 * i] = pack_bf16(ex2(s[4 * i]), ex2(s[4 * i + 1]));
      p[2 * i + 1] = pack_bf16(ex2(s[4 * i + 2]), ex2(s[4 * i + 3]));
    }
  }
}
#define L8 (8u << 16)
__device__ __forceinline__ uint64_t mk64(uint32_t lo, uint32_t hi) { uint64_t r; asm("mov.b64 %0, {%1, %2};" : "=l"(r) : "r"(lo), "r"(hi)); return r; }
__device__ __forceinline__ void adv(uint64_t& d) { asm volatile("{\n.reg .b32 l, h;\nmov.b64 {l, h}, %0;\nadd.u32 l, l, 768;\nmov.b64 %0, {l, h};\n}\n" : "+l"(d)); }
template <int J> __device__ __forceinline__ void attn_step(float (&s)[32], uint32_t (&p)[16], float (&o)[12], uint64_t qa1, uint64_t qa2,
                                                           uint64_t (&dk)[4], uint64_t (&dv)[8], const PC& pc) {
  fence_regs(s); fence_regs(p);
  softmax64(s, p, pc);
  fence_regs(p); fence_regs(s);
  wg_fence();
  wg_qk<0>(s, qa1, dk[J]); adv(dk[J]);
  wg_qk<1>(s, qa2, dk[J + 1]); adv(dk[J + 1]);
  wg_commit();
#pragma unroll
  for (int i = 0; i < 4; i++) { wg_pv(o, p[4 * i], p[4 * i + 1], p[4 * i + 2], p[4 * i + 3], dv[2 * J + i]); adv(dv[2 * J + i]); }
  wg_commit();
  wg_wait<1>();
}
__device__ __forceinline__ void attn_fast(uint32_t qa, float (&o)[12], uint32_t sb, const PC& pc, int pass, uint32_t zero) {
  const uint32_t kb = sb >> 4, hi = 16u + zero;
  float s[32];
  uint32_t pA[16], pB[16];
#pragma unroll
  for (int i = 0; i < 12; i++) o[i] = 0.f;
#pragma unroll
  for (int i = 0; i < 16; i++) { pA[i] = 0u; pB[i] = 0u; }
#pragma unroll
  for (int i = 0; i < 32; i++) s[i] = 0.f;
  const uint64_t qa1 = mk64(qa + L8, hi), qa2 = mk64(qa + 128u, 8u + zero);
  mbar_wait(sb + SM_MBAR + MB_KV, 0);
  wg_fence();
  wg_qk<0>(s, qa1, mk64(kb + L8, hi));
  wg_qk<1>(s, qa2, mk64(kb + 256, hi));
  wg_commit();
  wg_wait<0>();
  uint64_t dk[4], dv[8];
  dk[0] = mk64(kb + 128 + L8 + zero, hi); dk[1] = mk64(kb + 264 + zero * 2, hi);
  dk[2] = mk64(kb + 768 + L8 + zero * 3, hi); dk[3] = mk64(kb + 1024 + zero * 4, hi);
#pragma unroll
  for (int i = 0; i < 8; i++) dv[i] = mk64(kb + 384 + L8 + 48 * i + zero * (5 + i), hi);
#pragma unroll 1
  for (int c = 0; c < 16; c++) {
    if (pass == 0) mbar_wait(sb + SM_MBAR + MB_KV + (((c + 1) >> 1) & 7) * 8, 0);
    else if (c == 8 || c == 14) bar_arrive(c == 8 ? 10 : 9, NTHR);
    attn_step<0>(s, pA, o, qa1, qa2, dk, dv, pc);
    attn_step<2>(s, pB, o, qa1, qa2, dk, dv, pc);
    fence_regs(s);
  }
  wg_wait<0>();
  fence_regs(o); fence_regs(pA); fence_regs(pB);
}

__device__ __forceinline__ void attn_safe(uint32_t qa, float (&o)[12], uint32_t sb) {
  const uint32_t kb = sb >> 4;
  const uint64_t qa1 = mk64(qa + L8, 16u), qa2 = mk64(qa + 128u, 8u);
  float s[32];
  uint32_t p[16];
  float m0 = -INFINITY, m1 = -INFINITY;
#pragma unroll
  for (int i = 0; i < 32; i++) s[i] = 0.f;
#pragma unroll
  for (int i = 0; i < 12; i++) o[i] = 0.f;
#pragma unroll 1
  for (int u = 0; u < 32; u++) {
    if ((u & 3) == 0) mbar_wait(sb + SM_MBAR + MB_KV + (u >> 2) * 8, 0);
    const uint32_t kc = kb + (u >> 1) * 768;
    wg_fence();
    wg_qk<0>(s, qa1, mk64(kc + (u & 1) * 128 + L8, 16u));
    wg_qk<1>(s, qa2, mk64(kc + 256 + (u & 1) * 8, 16u));
    wg_commit();
    wg_wait<0>();
    fence_regs(s);
#pragma unroll
    for (int b = 0; b < 8; b++) {
      const float sc = ((PMASK >> b) & 1) ? 0.5f : 1.f;
      m0 = fmaxf(m0, sc * fmaxf(s[4 * b], s[4 * b + 1]));
      m1 = fmaxf(m1, sc * fmaxf(s[4 * b + 2], s[4 * b + 3]));
    }
  }
  m0 = fmaxf(m0, __shfl_xor_sync(~0u, m0, 1)); m0 = fmaxf(m0, __shfl_xor_sync(~0u, m0, 2));
  m1 = fmaxf(m1, __shfl_xor_sync(~0u, m1, 1)); m1 = fmaxf(m1, __shfl_xor_sync(~0u, m1, 2));
#pragma unroll 1
  for (int u = 0; u < 32; u++) {
    const uint32_t kc = kb + (u >> 1) * 768;
    wg_fence();
    wg_qk<0>(s, qa1, mk64(kc + (u & 1) * 128 + L8, 16u));
    wg_qk<1>(s, qa2, mk64(kc + 256 + (u & 1) * 8, 16u));
    wg_commit();
    wg_wait<0>();
    fence_regs(s);
#pragma unroll
    for (int b = 0; b < 8; b++) {
      const float sc = ((PMASK >> b) & 1) ? 0.5f : 1.f;
      p[2 * b] = pack_bf16(ex2(fmaf(s[4 * b], sc, -m0)), ex2(fmaf(s[4 * b + 1], sc, -m0)));
      p[2 * b + 1] = pack_bf16(ex2(fmaf(s[4 * b + 2], sc, -m1)), ex2(fmaf(s[4 * b + 3], sc, -m1)));
    }
    fence_regs(p);
    wg_fence();
#pragma unroll
    for (int i = 0; i < 4; i++) wg_pv(o, p[4 * i], p[4 * i + 1], p[4 * i + 2], p[4 * i + 3], mk64(kc + 384 + (u & 1) * 192 + 48 * i + L8, 16u));
    wg_commit();
    wg_wait<0>();
    fence_regs(o); fence_regs(p);
  }
}

__device__ __forceinline__ uint32_t movm(uint32_t a) { uint32_t r; asm volatile("movmatrix.sync.aligned.m8n8.trans.b16 %0, %1;" : "=r"(r) : "r"(a)); return r; }
__device__ __forceinline__ void mma_t(float (&d)[4], const uint4& w, uint32_t b0, uint32_t b1) {
  const uint32_t a0 = movm(w.x), a1 = movm(w.y), a2 = movm(w.z), a3 = movm(w.w);
  asm volatile("mma.sync.aligned.m16n8k16.row.col.f32.bf16.bf16.f32 {%0,%1,%2,%3}, {%4,%5,%6,%7}, {%8,%9}, {%0,%1,%2,%3};"
               : "+f"(d[0]), "+f"(d[1]), "+f"(d[2]), "+f"(d[3]) : "r"(a0), "r"(a1), "r"(a2), "r"(a3), "r"(b0), "r"(b1));
}
__device__ __forceinline__ float pick4(const float (&d)[4], int c) { return (c & 1) ? ((c & 2) ? d[3] : d[2]) : ((c & 2) ? d[1] : d[0]); }
__device__ __forceinline__ uint32_t ldg_nc1(const void* p) { uint32_t v; asm volatile("ld.global.nc.L1::no_allocate.u32 %0, [%1];" : "=r"(v) : "l"(p)); return v; }
__device__ __forceinline__ uint32_t ldg_ord(const void* p) { uint32_t v; asm volatile("ld.global.ca.u32 %0, [%1];" : "=r"(v) : "l"(p) : "memory"); return v; }
__device__ __forceinline__ uint32_t w_slot(int idx, int& goff) {
  const int k = idx / 9, nb = idx - k * 9;
  goff = k * DM + nb * 8;
  return nb * WNB + k * 16;
}
template <int BAR, int BN> __device__ __forceinline__ void ksplit_reduce(float (&res)[20], const float (&acc)[36], float* mine, const float* other, int d16, bool hi, int mh) {
#pragma unroll
  for (int i = 0; i < 20; i++) mine[i < 16 ? i * 128 : d16 + (i - 16) * 128] = hi ? acc[i] : acc[i < 16 ? 20 + i : 0];
  bar_sync(BN == 256 ? BAR + mh : BAR, BN);
#pragma unroll
  for (int i = 0; i < 20; i++) res[i] = (hi ? acc[i < 16 ? 20 + i : 0] : acc[i]) + other[i < 16 ? i * 128 : d16 + (i - 16) * 128];
}

__global__ void __launch_bounds__(NTHR, 1)
fused_kernel(const __grid_constant__ CUtensorMap xmap, const __nv_bfloat16* __restrict__ x, const __nv_bfloat16* __restrict__ wq,
             const __nv_bfloat16* __restrict__ wk, const __nv_bfloat16* __restrict__ wv, const __nv_bfloat16* __restrict__ wo,
             const __nv_bfloat16* __restrict__ w_r, const __nv_bfloat16* __restrict__ w_gate, const __nv_bfloat16* __restrict__ w_up,
             const __nv_bfloat16* __restrict__ w_down, const __nv_bfloat16* __restrict__ gate_w, __nv_bfloat16* __restrict__ out, uint32_t zero) {
  extern __shared__ __align__(1024) uint8_t smem[];
  const uint32_t sb = (uint32_t)__cvta_generic_to_shared(smem);
  const uint32_t mb = sb + SM_MBAR;
  TS(0);
  if (__any_sync(0xffffffffu, threadIdx.x >= 512)) {
    asm volatile("setmaxnreg.dec.sync.aligned.u32 64;");
    IDS
    unsigned tgt = 0;
    if (t128 == 0) {
#pragma unroll
      for (int i = 0; i < 21; i++) asm volatile("mbarrier.init.shared::cta.b64 [%0], 1;" ::"r"(mb + i * 8) : "memory");
      asm volatile("mbarrier.init.shared::cta.b64 [%0], 384;" ::"r"(mb + MB_W1) : "memory");
      asm volatile("mbarrier.init.shared::cta.b64 [%0], 128;" ::"r"(mb + MB_W3) : "memory");
      fence_async();
    }
    __syncthreads();
    if (t128 == 0) {
#pragma unroll
      for (int i = 0; i < 9; i++) {
        asm volatile("mbarrier.arrive.expect_tx.shared::cta.b64 _, [%0], 16384;" ::"r"(mb + MB_X + i * 8) : "memory");
        asm volatile("cp.async.bulk.tensor.2d.shared::cluster.global.mbarrier::complete_tx::bytes [%0], [%1, {%3, %4}], [%2];"
                     ::"r"(sb + i * 16384), "l"((uint64_t)&xmap), "r"(mb + MB_X + i * 8), "r"(i * 64), "r"(tb * 128) : "memory");
      }
      if (hg >= 6) tgt = ticket_arrive(&g_ctr[0], NCTA);
    }
    {
      const __nv_bfloat16* w = wq + hg * 72;
#pragma unroll
      for (int i = 0; i < 12; i++) { int go; uint32_t so = w_slot(tid - 256 + 384 * i, go); cp_async16(sb + SM_W1 + so, w + go); }
      uint4 lw[5];
#pragma unroll
      for (int i = 0; i < 5; i++) { int go; w_slot(4608 + t128 + 128 * i, go); if (t128 + 128 * i < 576) lw[i] = ldg_nc(w + go); }
      if (hg < 6) bar_sync(8, 384);
#pragma unroll
      for (int i = 0; i < 5; i++) { int go; uint32_t so = w_slot(4608 + t128 + 128 * i, go); if (t128 + 128 * i < 576) *(uint4*)(smem + SM_W1 + so) = lw[i]; }
      cp_async_wait_all();
      fence_async();
      mbar_arrive(mb + MB_W1);
    }
    if (hg < 6) {
      bar_sync(3, 384);
      if (t128 == 0) tgt = ticket_arrive(&g_ctr[0], NCTA);
    }
    if (t128 == 0) {
      prefetch_l2((const uint8_t*)w_gate + bid * 41472, 41472);
      prefetch_l2((const uint8_t*)w_up + bid * 41472, 41472);
      prefetch_l2((const uint8_t*)w_down + bid * 41472, 41472);
      prefetch_l2((const uint8_t*)wo + bid * 5184, 5184);
      ticket_wait(&g_ctr[0], tgt);
      fence_async_g();
      TS2(5);
    }
    uint4 kn[4];
    if (wi == 0) {
      __syncwarp();
#pragma unroll
      for (int i = 0; i < 4; i++) kn[i] = ldg_cg(&g_kn[lane + 32 * i]);
    }
    bar_sync(9, NTHR);
    if (t128 == 0) {
#pragma unroll
      for (int i = 0; i < 8; i++) bulk_load(sb + i * 24576, (const uint8_t*)g_kv + i * 24576, 24576, mb + MB_KV + i * 8);
    }
    if (wi == 0) {
      __syncwarp();
      uint32_t km = 0u;
#pragma unroll
      for (int i = 0; i < 4; i++) km = max(km, __float_as_uint(__uint_as_float(kn[i].x) + __uint_as_float(kn[i].y) + __uint_as_float(kn[i].z)));
      float kmax;
      asm("sqrt.approx.f32 %0, %1;" : "=f"(kmax) : "f"(__uint_as_float(__reduce_max_sync(~0u, km))));
      if (lane == 0) *(volatile float*)(smem + SM_MISC + 292) = kmax;
      __syncwarp();
      bar_arrive(11, 544);
    }
    const bool odd = __any_sync(~0u, bid & 1);
    const int f0 = (bid >> 1) * 72 + (odd ? 40 : 0);
    const __nv_bfloat16 *pg = w_gate + (size_t)(wi * 144 + g) * FF + f0 + c * 8, *pu = w_up + (size_t)(wi * 144 + g) * FF + f0 + c * 8;
    uint4 wb[5][2];
#pragma unroll
    for (int i = 0; i < 3; i++) { wb[i][0] = ldg_nc(pg + (size_t)i * 8 * FF); wb[i][1] = ldg_nc(pu + (size_t)i * 8 * FF); }
    unsigned long long best = 0ull;
#pragma unroll
    for (int i = 0; i < 4; i++) { unsigned long long b2 = __ldcg(&g_best[lane + 32 * i]); best = b2 > best ? b2 : best; }
#pragma unroll
    for (int o = 1; o < 32; o <<= 1) { unsigned long long b2 = __shfl_xor_sync(~0u, best, o); best = b2 > best ? b2 : best; }
    const int sel = (int)(~(uint32_t)best) & (S_LEN - 1);
    uint32_t rb = (uint32_t)(best >> 32);
    rb = (rb & 0x80000000u) ? (rb & 0x7FFFFFFFu) : ~rb;
    const float rsel = rbf(sigmoidf_(__uint_as_float(rb)));
    float* m1 = (float*)(smem + SM_SV);
    uint8_t* hq = smem + SM_SV + 1280;
    const int cb = (g >> 1) * 8 + (g & 1) + c * 2;
    {
      uint8_t* xq = smem + SM_SV + 1600 + wi * 1152;
      const uint32_t* xp = (const uint32_t*)(x + (size_t)sel * DM + wi * 144);
#pragma unroll
      for (int i = 0; i < 3; i++)
        if (lane + 32 * i < 72) { const uint32_t v = ldg_nc1(xp + lane + 32 * i); *(uint4*)(xq + (lane + 32 * i) * 16) = make_uint4(v, 0u, 0u, v); }
#pragma unroll
      for (int i = 3; i < 5; i++) { wb[i][0] = ldg_nc(pg + (size_t)i * 8 * FF); wb[i][1] = ldg_nc(pu + (size_t)i * 8 * FF); }
      if (t128 < 40) *(uint32_t*)(hq + (t128 >> 1) * 16 + 4 + (t128 & 1) * 4) = 0u;
      __syncwarp();
      float ag[4] = {0.f, 0.f, 0.f, 0.f}, au[4] = {0.f, 0.f, 0.f, 0.f};
      const uint8_t* xb = xq + c * 16;
      const int eo = 32 - c * 6;
#pragma unroll
      for (int i = 0; i < 18; i++) {
        const int s = i % 5;
        const uint2 b = *(const uint2*)(xb + (g & 1) * 8 + i * 64);
        mma_t(ag, wb[s][0], b.x, b.y); mma_t(au, wb[s][1], b.x, b.y);
        if (i < 13) { wb[s][0] = ldg_nc(pg + (size_t)(i + 5) * 8 * FF); wb[s][1] = ldg_nc(pu + (size_t)(i + 5) * 8 * FF); }
        else if (!odd) {
#pragma unroll
          for (int h = 0; h < 2; h++) {
            const int p = (i - 13) * 2 + h;
            if (p < 9) {
              wb[s][h].x = ldg_nc1(pg + eo + (size_t)p * 16 * FF); wb[s][h].y = ldg_nc1(pu + eo + (size_t)p * 16 * FF);
              wb[s][h].z = ldg_nc1(pg + eo + (size_t)(p * 16 + 8) * FF); wb[s][h].w = ldg_nc1(pu + eo + (size_t)(p * 16 + 8) * FF);
            }
          }
        }
      }
      m1[wi * 80 + cb] = pick4(ag, c); m1[wi * 80 + 40 + cb] = pick4(au, c);
      if (!odd) {
        float ae[4] = {0.f, 0.f, 0.f, 0.f};
#pragma unroll
        for (int p = 0; p < 9; p++) mma_t(ae, wb[(13 + (p >> 1)) % 5][p & 1], *(const uint32_t*)(xb + p * 128), *(const uint32_t*)(xb + p * 128 + 64));
        if (c == 0) { m1[wi * 80 + 32 + g] = ae[0]; m1[wi * 80 + 72 + g] = ae[2]; }
      }
    }
    TS2(9);
    {
      const __nv_bfloat16* pd = w_down + (size_t)(f0 + g) * DM + wi * 64 + c * 8;
#pragma unroll
      for (int r = 0; r < 5; r++) if (r < 4 || !odd) { wb[r][0] = ldg_nc(pd + r * 8 * DM); wb[r][1] = ldg_nc(pd + r * 8 * DM + 32); }
      bar_sync(13, 128);
      if (t128 < 40) {
        const float gs = rbf((m1[t128] + m1[80 + t128]) + (m1[160 + t128] + m1[240 + t128]));
        const float us = rbf((m1[40 + t128] + m1[120 + t128]) + (m1[200 + t128] + m1[280 + t128]));
        const uint16_t hv = (uint16_t)pack_bf16(rbf(gs * sigmoidf_(gs)) * us, 0.f);
        uint8_t* hp = hq + (t128 >> 1) * 16 + (t128 & 1) * 2;
        *(uint16_t*)hp = hv; *(uint16_t*)(hp + 12) = hv;
      }
      bar_sync(13, 128);
      const uint8_t* hb = hq + c * 16 + (g & 1) * 8;
      float* yp = g_ypart + bid * DM + wi * 64 + cb;
      const int lo = 512 + (wi & 1) * 32 - wi * 64;
#pragma unroll
      for (int i = 0; i < 3; i++) {
        float a0[4] = {0.f, 0.f, 0.f, 0.f}, a1[4] = {0.f, 0.f, 0.f, 0.f};
#pragma unroll
        for (int r = 0; r < 5; r++) {
          if (r < 4 || !odd) {
            const uint2 b = *(const uint2*)(hb + r * 64);
            mma_t(a0, wb[r][0], b.x, b.y);
            if (i < 2) mma_t(a1, wb[r][1], b.x, b.y);
            if (i == 0) { wb[r][0] = ldg_nc(pd + r * 8 * DM + 256); wb[r][1] = ldg_nc(pd + r * 8 * DM + 256 + 32); }
            if (i == 1) wb[r][0] = ldg_nc(pd + lo + r * 8 * DM);
          }
        }
        if (i < 2) { yp[i * 256] = pick4(a0, c); yp[i * 256 + 32] = pick4(a1, c); }
        else if (wi < 2) yp[lo] = pick4(a0, c);
      }
    }
    bar_sync(13, 128);
    if (t128 == 0) { tgt = ticket_arrive(&g_ctr[32 * 17], NCTA); *(volatile int*)(smem + SM_MISC + 288) = sel; }
    TS2(10);
    if ((sel >> 7) == tb) {
      if (t128 == 0) ticket_wait(&g_ctr[32 * 17], tgt);
      bar_sync(13, 128);
      if (lane < 18) {
        float4 s = make_float4(0.f, 0.f, 0.f, 0.f);
        const float* yp = g_ypart + wi * 32 * DM + hg * 72 + lane * 4;
#pragma unroll 1
        for (int b = 0; b < 4; b++) {
          uint4 v[8];
#pragma unroll
          for (int i = 0; i < 8; i++) v[i] = ldg_cg(yp + (b * 8 + i) * DM);
#pragma unroll
          for (int i = 0; i < 8; i++) { s.x += __uint_as_float(v[i].x); s.y += __uint_as_float(v[i].y); s.z += __uint_as_float(v[i].z); s.w += __uint_as_float(v[i].w); }
        }
        *(float4*)(m1 + wi * 72 + lane * 4) = s;
      }
      bar_sync(13, 128);
      if (t128 < 72) ((float*)(smem + SM_MISC))[t128] = rbf(rbf((m1[t128] + m1[72 + t128]) + (m1[144 + t128] + m1[216 + t128])) * rsel);
    }
    bar_sync(10, NTHR);
    if (t128 == 0) tgt = ticket_arrive(&g_ctr[32 * (1 + tb) + 16], 8);
    {
      if (t128 < 108) {
        int go;
        const uint32_t so = sb + SM_W3 + w_slot(t128, go);
        const __nv_bfloat16* w = wo + hg * 72 + go;
#pragma unroll
        for (int i = 0; i < 48; i++) cp_async16(so + i * 192, w + i * 12 * DM);
      }
      cp_async_wait_all();
      fence_async();
      mbar_arrive(mb + MB_W3);
    }
    TS2(15);
    bar_sync(9, NTHR);
    if (t128 == 0) {
      ticket_wait(&g_ctr[32 * (1 + tb) + 16], tgt);
      fence_async_g();
#pragma unroll
      for (int i = 0; i < 2; i++) bulk_load(sb + SM_O + i * 36864, (const uint8_t*)g_o + tb * 147456 + 2 * i * 36864, 36864, mb + MB_O + i * 8);
    }
    bar_sync(12, NTHR);
    if (t128 == 0) {
      tgt = ticket_arrive(&g_ctr[32 * (1 + tb)], 8);
      ticket_wait(&g_ctr[32 * (1 + tb)], tgt);
      fence_async_g();
      TS2(11);
#pragma unroll
      for (int i = 0; i < 2; i++) bulk_load(sb + SM_O + (2 + i) * 36864, (const uint8_t*)g_o + tb * 147456 + (2 * i + 1) * 36864, 36864, mb + MB_O + (2 + i) * 8);
    }
    return;
  }

  asm volatile("setmaxnreg.inc.sync.aligned.u32 104;");
  {
  IDS
  const bool khu = __any_sync(0xffffffffu, kh != 0);
  if (khu) {
    if (tid == 256) prefetch_l2((const uint8_t*)wq + bid * 5184, 5184);
    __syncthreads();
    const __nv_bfloat16* w = wq + hg * 72;
#pragma unroll
    for (int i = 0; i < 12; i++) { int go; uint32_t so = w_slot(tid - 256 + 384 * i, go); cp_async16(sb + SM_W1 + so, w + go); }
  } else if (hg < 6) {
    uint4 ev[3];
#pragma unroll
    for (int i = 0; i < 3; i++) {
      const int k = min(tid + 256 * i, DM - 1);
      const uint32_t* src = (const uint32_t*)((hg < 3 ? wk : wv) + k * 18) + (hg % 3) * 4;
      const bool l2 = hg % 3 == 2;
      ev[i].x = ldg_ord(src);
      ev[i].y = ldg_ord(l2 ? (const uint32_t*)w_r + (k >> 1) : src + 1);
      ev[i].z = ldg_ord(l2 ? (const uint32_t*)gate_w + (k >> 1) : src + 2);
      ev[i].w = ldg_ord(l2 ? src : src + 3);
    }
    __syncthreads();
#pragma unroll
    for (int i = 0; i < 3; i++) {
      const int k = tid + 256 * i;
      if (hg % 3 == 2) { ev[i].y = hg == 2 ? __byte_perm(ev[i].y, ev[i].z, (k & 1) ? 0x7632 : 0x5410) : 0u; ev[i].z = 0u; ev[i].w = 0u; }
      if (k < DM) *(uint4*)(smem + SM_W1 + (k >> 6) * WNB + 8192 + (k & 63) * 16) = ev[i];
    }
    fence_async();
    bar_sync(1, 256);
  } else {
    __syncthreads();
  }
  const uint64_t ad = make_desc(sb + mh * 8192, 16, 1024) | (1ull << 62);
  if (khu) {
    cp_async_wait_all();
    fence_async();
    mbar_arrive(mb + MB_W1);
  } else if (hg < 6) {
    float e[4] = {0.f, 0.f, 0.f, 0.f};
    const uint64_t ed = make_desc(sb + SM_W1 + 8192, 128, 128);
#pragma unroll 1
    for (int b = 0; b < 9; b++) {
      mbar_wait(mb + MB_X + b * 8, 0);
      wg_fence();
#pragma unroll
      for (int j = 0; j < 4; j++) wgmma_t(e, ad + (uint64_t)(b * 1024 + j * 2), ed + (uint64_t)(b * (WNB / 16) + j * 16), 1);
      wg_commit();
    }
    wg_wait<0>();
    fence_regs(e);
    bar_arrive(8, 384);
    TS(1);
    const int ch = hg % 3;
    float nrm = 0.f;
    unsigned long long best = 0ull;
#pragma unroll
    for (int h = 0; h < 2; h++) {
      const int key = tb * 128 + lrow + 8 * h;
      const bool poly = (PMASK >> ((key >> 3) & 7)) & 1;
      uint32_t v = pack_bf16(e[2 * h], e[2 * h + 1]);
      if (hg < 3) {
        float lo = bf_lo(v), hi = bf_hi(v);
        float n2 = (hg == 2 && c != 0) ? 0.f : lo * lo + hi * hi;
        n2 += __shfl_xor_sync(~0u, n2, 1);
        n2 += __shfl_xor_sync(~0u, n2, 2);
        nrm = fmaxf(nrm, n2);
        if (hg == 2 && c == 1) {
          g_gate[key] = hi;
          uint32_t rb = __float_as_uint(lo);
          rb = (rb & 0x80000000u) ? ~rb : (rb | 0x80000000u);
          unsigned long long cand = ((unsigned long long)rb << 32) | (uint32_t)(~key);
          best = cand > best ? cand : best;
        }
        if (poly) v = pack_bf16(2.f * lo, 2.f * hi);
        if (hg == 2 && c != 0) v = c == 1 ? (poly ? 0x44404000u : 0x00003F80u) : (c == 2 && poly ? 0x0000BFFFu : 0u);
      } else if (hg == 5 && c != 0) {
        v = c == 1 ? 0x00003F80u : 0u;
      }
      const int kb8 = (lrow >> 3) + h;
      const int off = hg >= 3 ? 6144 + (kb8 >> 1) * 768 + ch * 256 + (kb8 & 1) * 128 : hg == 2 ? 4096 + (kb8 & 7) * 256 + (kb8 >> 3) * 128 : kb8 * 256 + ch * 128;
      uint8_t* dst = (uint8_t*)g_kv + tb * 12288 + off + g * 16 + c * 4;
      *(uint32_t*)dst = v;
    }
    if (hg < 3) {
      nrm = __uint_as_float(__reduce_max_sync(~0u, __float_as_uint(nrm)));
      if (lane == 0) ((float*)&g_kn[tb * 8 + mh * 4 + wi])[hg] = nrm;
      if (hg == 2) {
        const uint32_t bh = __reduce_max_sync(~0u, (uint32_t)(best >> 32));
        const uint32_t bl = __reduce_max_sync(~0u, (uint32_t)(best >> 32) == bh ? (uint32_t)best : 0u);
        if (lane == 0) g_best[tb * 8 + mh * 4 + wi] = ((unsigned long long)bh << 32) | bl;
      }
    }
    fence_async_g();
    bar_arrive(3, 384);
    TS(2);
  }
  {
    float acc0[36], acc[20];
#pragma unroll
    for (int j = 0; j < 36; j++) acc0[j] = 0.f;
    mbar_wait(mb + MB_W1, 0);
#pragma unroll 1
    for (int b = 0; b < 5; b++) mbar_wait(mb + MB_X + ((khu ? 4 : 0) + b) * 8, 0);
    TS(3);
    const uint64_t wd = make_desc(sb + SM_W1 + (khu ? 4608 : 0), 128, WNB);
    const int k0 = khu ? 18 : 0;
    wg_fence();
#pragma unroll
    for (int j = 0; j < 18; j++) wgmma_t(acc0, ad + (uint64_t)(((k0 + j) >> 2) * 1024 + ((k0 + j) & 3) * 2), wd + (uint64_t)(j * 16), 1);
    wg_commit();
    wg_wait<0>();
    fence_regs(acc0);
    ksplit_reduce<14, 512>(acc, acc0, (float*)(smem + (khu ? 7 : 0) * 16384 + mh * 8192) + t128, (const float*)(smem + (khu ? 0 : 7) * 16384 + mh * 8192) + t128,
                           4096, khu, mh);
    const float qs = 0.23570226039551584f * 1.4426950408889634f;
    uint8_t* qp = smem + SM_Q + mh * 12288 + g * 16;
#pragma unroll
    for (int nb = 0; nb < 5; nb++) {
      if (nb < 4 || kh == 0) {
        const int col = kh * 40 + nb * 8 + 2 * c, hd = (col * 57) >> 10, d = col - hd * 18;
        const float sc = d >= 16 ? 0.5f : 1.f;
        uint8_t* p0 = qp + hd * 3072 + (d >= 16 ? 2048 + wi * 256 : wi * 512 + (d >> 3) * 128 + (d & 7) * 2);
        *(uint32_t*)p0 = pack_bf16(rbf(acc[4 * nb] * qs) * sc, rbf(acc[4 * nb + 1] * qs) * sc);
        *(uint32_t*)(p0 + (d >= 16 ? 128 : 256)) = pack_bf16(rbf(acc[4 * nb + 2] * qs) * sc, rbf(acc[4 * nb + 3] * qs) * sc);
      }
    }
  }
  fence_async();
  TS(4);
  bar_arrive(9, NTHR);
  bar_sync(14, 512);
  }
  {
    uint32_t unsafe;
    {
      IDS
      uint8_t* qp = smem + SM_Q + wg * 3072 + g * 16 + c * 4;
      float nn[4];
#pragma unroll
      for (int i = 0; i < 4; i++) {
        const uint8_t* p0 = qp + (i >> 1) * 12288 + (wi * 2 + (i & 1)) * 256;
        const uint32_t q0 = *(const uint32_t*)p0, q1 = *(const uint32_t*)(p0 + 128);
        const uint32_t q2 = c == 0 ? *(const uint32_t*)(qp + (i >> 1) * 12288 + 2048 + (wi * 2 + (i & 1)) * 128) : 0u;
        float n = bf_lo(q0) * bf_lo(q0) + bf_hi(q0) * bf_hi(q0) + bf_lo(q1) * bf_lo(q1) + bf_hi(q1) * bf_hi(q1) + 4.f * (bf_lo(q2) * bf_lo(q2) + bf_hi(q2) * bf_hi(q2));
        n += __shfl_xor_sync(~0u, n, 1); n += __shfl_xor_sync(~0u, n, 2);
        nn[i] = sqrtf(n) * 1.001f;
      }
      bar_sync(11, 544);
      const float kmax = *(volatile float*)(smem + SM_MISC + 292);
      bool ok = true;
#pragma unroll
      for (int i = 0; i < 4; i++) { nn[i] = ceilf(fmaf(nn[i], kmax, 0.01f)); ok = ok && nn[i] <= 60.f; }
      asm volatile("{\n.reg .pred p, r;\nsetp.ne.u32 p, %1, 0;\nbarrier.cta.red.or.pred.aligned r, %2, 128, p;\nselp.u32 %0, 1, 0, r;\n}\n"
                   : "=r"(unsafe) : "r"((uint32_t)!ok), "r"(4 + wg) : "memory");
#pragma unroll
      for (int i = 0; i < 4; i++) {
        const uint32_t v = unsafe ? 0u : c == 1 ? pack_bf16(-0.5f * nn[i], 0.5f) : c == 2 ? 0x3F003F00u : 0u;
        if (c != 0) *(uint32_t*)(qp + (i >> 1) * 12288 + 2048 + (wi * 2 + (i & 1)) * 128) = v;
      }
      fence_async();
      bar_sync(4 + wg, 128);
    }
    PC pc; pc.msk = 0x007F007Fu + zero; pc.cb = 0x3EF33EF3u + zero;
    const uint32_t qa0 = ((sb + SM_Q) >> 4) + __shfl_sync(~0u, threadIdx.x >> 7, 0) * 192;
#pragma unroll 1
    for (int pass = 0; pass < 2; pass++) {
      float o[12];
      TS(6 + pass);
      if (!__any_sync(0xffffffffu, unsafe)) {
        attn_fast(qa0 + pass * 768, o, sb, pc, pass, zero);
      } else {
        attn_safe(qa0 + pass * 768, o, sb);
        if (pass == 1) { bar_arrive(10, NTHR); bar_arrive(9, NTHR); }
      }
      IDS
      const float i0 = 1.f / __shfl_sync(~0u, o[8], (lane & ~3) | 1), i1 = 1.f / __shfl_sync(~0u, o[10], (lane & ~3) | 1);
      uint8_t* ob = (uint8_t*)g_o + tb * 147456 + (pass + 2 * (hg >> 2)) * 36864 + wi * 9216 + g * 16;
      const int c0 = (hg & 3) * 72 + wg * 18 + 2 * c;
      uint8_t* p0 = ob + (c0 >> 3) * 128 + (c0 & 7) * 2;
      *(uint32_t*)p0 = pack_bf16(o[0] * i0, o[1] * i0); *(uint32_t*)(p0 + 4608) = pack_bf16(o[2] * i1, o[3] * i1);
      *(uint32_t*)(p0 + 128) = pack_bf16(o[4] * i0, o[5] * i0); *(uint32_t*)(p0 + 4608 + 128) = pack_bf16(o[6] * i1, o[7] * i1);
      if (c == 0) { *(uint32_t*)(p0 + 256) = pack_bf16(o[8] * i0, o[9] * i0); *(uint32_t*)(p0 + 4608 + 256) = pack_bf16(o[10] * i1, o[11] * i1); }
      fence_async_g();
    }
  }
  TS(8);
  bar_arrive(12, NTHR);

  {
    IDS
    const bool khu = __any_sync(0xffffffffu, kh != 0);
    const int row = tb * 128 + lrow;
    const int nb0 = kh == 0 ? 0 : 5;
    uint32_t xr[10];
    {
      const uint32_t* xp = (const uint32_t*)(x + (size_t)row * DM + hg * 72 + nb0 * 8) + c;
#pragma unroll
      for (int i = 0; i < 5; i++) {
        xr[2 * i] = (i < 4 || kh == 0) ? __ldg(xp + i * 4) : 0u;
        xr[2 * i + 1] = (i < 4 || kh == 0) ? __ldg(xp + 4 * DM + i * 4) : 0u;
      }
    }
    const float g0 = rbf(sigmoidf_(__ldcg(&g_gate[row]))), g1 = rbf(sigmoidf_(__ldcg(&g_gate[row + 8])));
    float acc0[36], acc[20];
    const int slot = (wg & 1) * 2 + (wg >> 1);
    {
      const uint64_t ad = make_desc(sb + SM_O + slot * 36864, 128, 4608), wd = make_desc(sb + SM_W3 + (khu ? 4608 : 0), 128, WNB);
#pragma unroll
      for (int j = 0; j < 36; j++) acc0[j] = 0.f;
      mbar_wait(mb + MB_W3, 0);
      mbar_wait(mb + MB_O + slot * 8, 0);
      TS(12);
      wg_fence();
#pragma unroll
      for (int j = 0; j < 18; j++) wgmma_t(acc0, ad + (uint64_t)(j * 16), wd + (uint64_t)(j * 16), 1);
      wg_commit();
      wg_wait<0>();
      fence_regs(acc0);
    }
    ksplit_reduce<1, 256>(acc, acc0, (float*)(smem + SM_O + slot * 36864) + t128, (const float*)(smem + SM_O + (slot ^ 1) * 36864) + t128, 2048, khu, mh);
    TS(13);
    const float* upd = (const float*)(smem + SM_MISC);
    const int sel = *(volatile int*)(smem + SM_MISC + 288);
    const float h0 = rbf(1.f - g0), h1 = rbf(1.f - g1);
    uint32_t* op = (uint32_t*)(out + (size_t)row * DM + hg * 72 + nb0 * 8) + c;
#pragma unroll
    for (int i = 0; i < 5; i++) {
      if (i < 4 || kh == 0) {
        const float a0 = acc[4 * i], a1 = acc[4 * i + 1], a2 = acc[4 * i + 2], a3 = acc[4 * i + 3];
        const uint32_t x0 = xr[2 * i], x1 = xr[2 * i + 1];
        float b0 = bf_lo(x0), b1 = bf_hi(x0), b2 = bf_lo(x1), b3 = bf_hi(x1);
        const int col = (nb0 + i) * 8 + c * 2;
        if (row == sel) { b0 = rbf(b0 + upd[col]); b1 = rbf(b1 + upd[col + 1]); }
        if (row + 8 == sel) { b2 = rbf(b2 + upd[col]); b3 = rbf(b3 + upd[col + 1]); }
        op[i * 4] = pack_bf16(rbf(g0 * rbf(a0)) + rbf(h0 * b0), rbf(g0 * rbf(a1)) + rbf(h0 * b1));
        op[4 * DM + i * 4] = pack_bf16(rbf(g1 * rbf(a2)) + rbf(h1 * b2), rbf(g1 * rbf(a3)) + rbf(h1 * b3));
      }
    }
    TS(14);
  }
}

typedef CUresult (*EncodeFn)(CUtensorMap*, CUtensorMapDataType, cuuint32_t, void*, const cuuint64_t*, const cuuint64_t*, const cuuint32_t*,
                             const cuuint32_t*, CUtensorMapInterleave, CUtensorMapSwizzle, CUtensorMapL2promotion, CUtensorMapFloatOOBfill);

extern "C" void kernel_launch(void* const* d_in, const int* in_sizes, int n_in, void* d_out, int out_size) {
  static EncodeFn enc = nullptr;
  if (!enc) {
    cudaDriverEntryPointQueryResult qr;
    void* fn = nullptr;
    cudaGetDriverEntryPoint("cuTensorMapEncodeTiled", &fn, cudaEnableDefault, &qr);
    enc = (EncodeFn)fn;
    cudaFuncSetAttribute(fused_kernel, cudaFuncAttributeMaxDynamicSharedMemorySize, SM_TOTAL);
  }
  CUtensorMap xmap;
  const cuuint64_t gdim[2] = {DM, S_LEN}, gstr[1] = {DM * 2};
  const cuuint32_t box[2] = {64, 128}, estr[2] = {1, 1};
  enc(&xmap, CU_TENSOR_MAP_DATA_TYPE_BFLOAT16, 2, d_in[0], gdim, gstr, box, estr, CU_TENSOR_MAP_INTERLEAVE_NONE, CU_TENSOR_MAP_SWIZZLE_128B,
      CU_TENSOR_MAP_L2_PROMOTION_L2_128B, CU_TENSOR_MAP_FLOAT_OOB_FILL_NONE);
  typedef const __nv_bfloat16* P;
  fused_kernel<<<NCTA, NTHR, SM_TOTAL, cudaStreamPerThread>>>(xmap, (P)d_in[0], (P)d_in[1], (P)d_in[2], (P)d_in[3], (P)d_in[4], (P)d_in[6],
                                                             (P)d_in[7], (P)d_in[8], (P)d_in[9], (P)d_in[10], (__nv_bfloat16*)d_out, 0u);
}
```
